```python
import torch

def _softmax(x, axis=-1):
    return torch.softmax(x, dim=axis)

def _gelu(x):
    return torch.nn.functional.gelu(x, approximate='tanh')

def _silu(x):
    return torch.nn.functional.silu(x)

def _sigmoid(x):
    return torch.sigmoid(x)

def _layernorm(x, axis=-1, eps=1e-05):
    m = x.mean(dim=axis, keepdim=True)
    v = x.var(dim=axis, keepdim=True, unbiased=False)
    return (x - m) / torch.sqrt(v + eps)

def _scatter_add(tgt, idx, src, axis=0):
    return tgt.clone().index_add_(axis, idx, src)

def _segment_sum(src, seg, n):
    out = torch.zeros((n,) + src.shape[1:], dtype=src.dtype)
    return out.index_add_(0, seg, src)

def _pad(x, pw):
    flat = tuple((v for pair in reversed(pw) for v in pair))
    return torch.nn.functional.pad(x, flat)
kernel_name = 'adaLN_cond__sliding_block__glu_gated_geglu__prompt'

def setup_inputs():

    _w = lambda a: (lambda t: t.to(torch.bfloat16) if t.is_floating_point() else t)(torch.as_tensor(a))

    def _A_setup():
        B, S, D = (1, 2048, 640)
        return {'x': _w((lambda *s: torch.randn(*s, dtype=torch.bfloat16) * 0.05)(B, S, D)), 'wqkv': _w((lambda *s: torch.randn(*s, dtype=torch.bfloat16) * 0.05)(D, 3 * D)), 'wo': _w((lambda *s: torch.randn(*s, dtype=torch.bfloat16) * 0.05)(D, D))}
    _A_in = _A_setup()

    def _B_setup():
        B, S, Dm, Df = (1, 2048, 640, 1536)
        return {'x': _w((lambda *s: torch.randn(*s, dtype=torch.bfloat16) * 0.05)(B, S, Dm)), 'w_gate': _w((lambda *s: torch.randn(*s, dtype=torch.bfloat16) * 0.8)(Dm, Df) * Dm ** (-0.5)), 'w_up': _w((lambda *s: torch.randn(*s, dtype=torch.bfloat16) * 0.8)(Dm, Df) * Dm ** (-0.5)), 'w_down': _w((lambda *s: torch.randn(*s, dtype=torch.bfloat16) * 0.8)(Df, Dm) * Df ** (-0.5))}
    _B_in = _B_setup()
    return {'A_x': _A_in['x'], 'A_wqkv': _A_in['wqkv'], 'A_wo': _A_in['wo'], 'B_x': _B_in['x'], 'B_w_gate': _B_in['w_gate'], 'B_w_up': _B_in['w_up'], 'B_w_down': _B_in['w_down'], 'c': _w((lambda *s: torch.randn(*s, dtype=torch.bfloat16) * 0.2)(1, 640) * 8.0), 'w_mod': _w((lambda *s: torch.randn(*s, dtype=torch.bfloat16) * 0.2)(640, 6 * 640) * 640 ** (-0.5) * 8.0)}

def reference(A_x, A_wqkv, A_wo, B_x, B_w_gate, B_w_up, B_w_down, c, w_mod):

    def _A_ref(x, wqkv, wo):
        B, S, D = x.shape
        H = 32
        Dh = D // H
        W = 256
        qkv = (lambda x, *d: x.permute(*d))((x @ wqkv).reshape(B, S, 3, H, Dh), 2, 0, 3, 1, 4)
        q, k, v = (qkv[0], qkv[1], qkv[2])
        scores = torch.einsum('bhqd,bhkd->bhqk', q, k) * Dh ** (-0.5)
        idx = torch.arange(S)
        mask = (idx[:, None] - idx[None, :] >= 0) & (idx[:, None] - idx[None, :] < W)
        scores = torch.where(mask[None, None], scores, -1000000000.0)
        p = _softmax(scores, axis=-1)
        o = torch.einsum('bhqk,bhkd->bhqd', p, v)
        return (lambda x, *d: x.permute(*d))(o, 0, 2, 1, 3).reshape(B, S, D) @ wo

    def _B_ref(x, w_gate, w_up, w_down):
        g = torch.einsum('bsd,df->bsf', x, w_gate)
        u = torch.einsum('bsd,df->bsf', x, w_up)
        h = _gelu(g) * u
        return torch.einsum('bsf,fd->bsd', h, w_down)
    x = A_x
    mod = (_silu(c) @ w_mod).reshape(c.shape[0], 6, 1, -1)
    sa, ca, ga, sb, cb, gb = (mod[:, 0].clone(), mod[:, 1].clone(), mod[:, 2].clone(), mod[:, 3].clone(), mod[:, 4].clone(), mod[:, 5].clone())
    h = _layernorm(x, axis=-1) * (1 + ca) + sa
    x = x + ga * _A_ref(h, A_wqkv, A_wo)
    h = _layernorm(x, axis=-1) * (1 + cb) + sb
    x = x + gb * _B_ref(h, B_w_gate, B_w_up, B_w_down)
    return x
```

```cpp
#include <cuda_runtime.h>
#include <cuda.h>
#include <cuda_bf16.h>
#include <stdint.h>
#include <type_traits>

typedef __nv_bfloat16 bf16;

constexpr int SEQ = 2048, DM = 640;
constexpr int NCTA = 128;
constexpr int SPIN_LIMIT = 40000;

constexpr int KV_BYTES = 22 * 1024;
constexpr int O_BYTES = 10 * 1024;
constexpr int HH_BYTES = 24 * 1024;
__device__ __align__(1024) uint8_t g_kv[32 * 8 * KV_BYTES];
__device__ __align__(1024) uint8_t g_o[32 * 8 * O_BYTES];
__device__ __align__(1024) uint8_t g_x1[32 * 8 * O_BYTES];
__device__ __align__(1024) uint8_t g_h2[32 * 8 * O_BYTES];
__device__ __align__(1024) uint8_t g_hh[32 * 8 * HH_BYTES];
__device__ __align__(1024) uint8_t g_wd[192 * 10240];
__device__ __align__(128) uint32_t g_wdflag[8][32];
__device__ __align__(1024) unsigned long long g_st2[SEQ * 8];
__device__ __align__(128) unsigned long long g_st1[SEQ];
__device__ __align__(128) unsigned long long g_mod[1920];
__device__ __align__(128) uint32_t g_flag[4][32][32];
__device__ uint32_t g_slot[64];
__device__ uint32_t g_done;

constexpr int P1_STAGE = 53248;
constexpr int SM_P0 = 3 * P1_STAGE;
constexpr int SM_NS = 30720;
constexpr int SM_WO = 0, WO_SL = 12800;
constexpr int SM_KV = 81920;
constexpr int SM_ONES = 217088;
constexpr int SM_T = 102400;
constexpr int SM_XT = SM_T + 4 * 20480;
constexpr int SM_A4 = 0;
constexpr int SM_B4 = 81920, B4_STAGE = 24576;
__host__ __device__ constexpr int b4_off(int slot) { return SM_B4 + (slot < 3 ? slot + 2 : slot - 3) * B4_STAGE; }
constexpr int D_NST = 7;
constexpr int SM_X1 = 114688;
__host__ __device__ constexpr int da_off(int slot) { return ((0x4326150 >> (4 * slot)) & 7) * 16384; }
__host__ __device__ constexpr int db_off(int slot) { return slot < 4 ? 180224 + slot * 10240 : 135168 + (slot - 4) * 10240; }
constexpr int SM_BAR = 221184;
constexpr int SM_MOD1 = SM_BAR + 896;
constexpr int SM_MOD2 = SM_MOD1 + 2560;
constexpr int SM_SILU = SM_MOD2 + 2560;
constexpr int SM_GV = SM_SILU + 2560;
constexpr int SM_INFO = SM_GV + 320;
constexpr int SM_TOTAL = SM_INFO + 32;

enum { B_PF = 0, B_PE = 4,
       B_KVF = 8, B_KVS = 12,
       B_WOF = 13, B_TF = 21, B_TE = 25,
       B_AF = 29, B_AE = 33, B_BF = 37, B_BE = 42, B_XT = 47,
       B_DF = 48, B_DE = 55,
       B_PD = 62,
       B_PUB = 66,
       B_MODS = 78, B_M1 = 79, B_X1 = 81, B_MC = 82, B_G = 83, B_NS = 84, B_RP = 85, B_HQ = 86, B_XS = 90, B_KG = 91, B_H2 = 92,
       B_OS = 94, B_X1S = 95, B_NSL = 96, B_TB = 97, B_GO = 98,
       B_M0 = 99, B_M0B = 100, B_C = 101, B_XR = 102, B_COUNT = 103 };
__host__ __device__ constexpr int bar_count(int i) {
    return i < B_PE ? 2 : i < B_KVF ? 4 : i < B_KVS ? 1 : i == B_KVS ? 3 : i < B_TE ? 1 : i == B_TE + 3 ? 8 : i < B_AF ? 2 : i < B_AE ? 1
         : i < B_BF ? 8 : i < B_BE ? 1 : i < B_XT ? 4 : i < B_DE ? 1 : i == B_PD + 1 ? 2 : i < B_MODS ? 4
         : i == B_MC || i == B_G || i == B_NSL ? 2 : i == B_NS ? 6 : i >= B_KG && i < B_OS ? 4 : 1;
}
enum { EV_KV = 0, EV_O = 1, EV_X1 = 2, EV_HH = 3 };

__device__ __forceinline__ uint32_t smem_u32(const void* p) { return (uint32_t)__cvta_generic_to_shared(p); }
__device__ __forceinline__ void mbar_init(uint32_t bar, uint32_t cnt) { asm volatile("mbarrier.init.shared::cta.b64 [%0], %1;" ::"r"(bar), "r"(cnt)); }
__device__ __forceinline__ void mbar_expect_tx(uint32_t bar, uint32_t bytes) { asm volatile("mbarrier.arrive.expect_tx.shared::cta.b64 _, [%0], %1;" ::"r"(bar), "r"(bytes) : "memory"); }
__device__ __forceinline__ void mbar_arrive(uint32_t bar) { asm volatile("mbarrier.arrive.shared::cta.b64 _, [%0];" ::"r"(bar) : "memory"); }
__device__ __forceinline__ void mbar_arrive_cta(uint32_t bar, uint32_t cta) {
    asm volatile("{ .reg .b32 ra; mapa.shared::cluster.u32 ra, %0, %1; mbarrier.arrive.shared::cluster.b64 _, [ra]; }" ::"r"(bar), "r"(cta) : "memory");
}
__device__ __forceinline__ void mbar_wait(uint32_t bar, uint32_t parity) {
    asm volatile(
        "{ .reg .pred p; .reg .u32 n;\n"
        "mov.u32 n, 0;\n"
        "LW: mbarrier.try_wait.parity.shared::cta.b64 p, [%0], %1;\n"
        "@p bra LD;\n"
        "add.u32 n, n, 1;\n"
        "setp.lt.u32 p, n, %2;\n"
        "@p bra LW;\n"
        "LD: }" ::"r"(bar), "r"(parity), "n"(SPIN_LIMIT * 8) : "memory");
}
__device__ __forceinline__ void mbar_wait_long(uint32_t bar, uint32_t parity) {
    asm volatile(
        "{ .reg .pred p; .reg .u32 n;\n"
        "mov.u32 n, 0;\n"
        "LW: mbarrier.try_wait.parity.shared::cta.b64 p, [%0], %1, 4000;\n"
        "@p bra LD;\n"
        "add.u32 n, n, 1;\n"
        "setp.lt.u32 p, n, %2;\n"
        "@p bra LW;\n"
        "LD: }" ::"r"(bar), "r"(parity), "n"(SPIN_LIMIT / 4) : "memory");
}
__device__ __forceinline__ void bulk_load(uint32_t dst, const void* src, uint32_t bytes, uint32_t bar) {
    asm volatile("cp.async.bulk.shared::cluster.global.mbarrier::complete_tx::bytes [%0], [%1], %2, [%3];" ::"r"(dst), "l"(src), "r"(bytes), "r"(bar) : "memory");
}
__device__ __forceinline__ void bulk_load_mc(uint32_t dst, const void* src, uint32_t bytes, uint32_t bar) {
    asm volatile("cp.async.bulk.shared::cluster.global.mbarrier::complete_tx::bytes.multicast::cluster [%0], [%1], %2, [%3], %4;" ::"r"(dst), "l"(src), "r"(bytes), "r"(bar), "h"((uint16_t)3) : "memory");
}
__device__ __forceinline__ void bulk_push(uint32_t dst, uint32_t src, uint32_t bytes, uint32_t bar, uint32_t cta) {
    asm volatile("{ .reg .b32 rd, rb; mapa.shared::cluster.u32 rd, %0, %4; mapa.shared::cluster.u32 rb, %3, %4;\n"
                 "cp.async.bulk.shared::cluster.shared::cta.mbarrier::complete_tx::bytes [rd], [%1], %2, [rb]; }" ::"r"(dst), "r"(src), "r"(bytes), "r"(bar), "r"(cta) : "memory");
}
__device__ __forceinline__ void bulk_store(void* dst, uint32_t src, uint32_t bytes) {
    asm volatile("cp.async.bulk.global.shared::cta.bulk_group [%0], [%1], %2;" ::"l"(dst), "r"(src), "r"(bytes) : "memory");
}
__device__ __forceinline__ void bulk_commit_wait() {
    asm volatile("cp.async.bulk.commit_group;" ::: "memory");
    asm volatile("cp.async.bulk.wait_group 0;" ::: "memory");
}
__device__ __forceinline__ void l2_prefetch(const void* src, uint32_t bytes) {
    asm volatile("cp.async.bulk.prefetch.L2.global [%0], %1;" ::"l"(src), "r"(bytes) : "memory");
}
__device__ __forceinline__ void tma2d(uint32_t dst, const CUtensorMap* m, int c0, int c1, uint32_t bar) {
    asm volatile("cp.async.bulk.tensor.2d.shared::cluster.global.mbarrier::complete_tx::bytes [%0], [%1, {%3,%4}], [%2];" ::"r"(dst), "l"(m), "r"(bar), "r"(c0), "r"(c1) : "memory");
}
__device__ __forceinline__ void tma2d_store(const CUtensorMap* m, uint32_t src, int c0, int c1) {
    asm volatile("cp.async.bulk.tensor.2d.global.shared::cta.bulk_group [%0, {%2,%3}], [%1];" ::"l"(m), "r"(src), "r"(c0), "r"(c1) : "memory");
}
__device__ __forceinline__ void tma3d(uint32_t dst, const CUtensorMap* m, int c0, int c1, int c2, uint32_t bar) {
    asm volatile("cp.async.bulk.tensor.3d.shared::cluster.global.mbarrier::complete_tx::bytes [%0], [%1, {%3,%4,%5}], [%2];" ::"r"(dst), "l"(m), "r"(bar), "r"(c0), "r"(c1), "r"(c2) : "memory");
}
__device__ __forceinline__ void tma3d_mc(uint32_t dst, const CUtensorMap* m, int c0, int c1, int c2, uint32_t bar) {
    asm volatile("cp.async.bulk.tensor.3d.shared::cluster.global.mbarrier::complete_tx::bytes.multicast::cluster [%0], [%1, {%3,%4,%5}], [%2], %6;" ::"r"(dst), "l"(m), "r"(bar), "r"(c0), "r"(c1), "r"(c2), "h"((uint16_t)3) : "memory");
}
__device__ __forceinline__ void tma4d_mc(uint32_t dst, const CUtensorMap* m, int c0, int c1, int c2, int c3, uint32_t bar) {
    asm volatile("cp.async.bulk.tensor.4d.shared::cluster.global.mbarrier::complete_tx::bytes.multicast::cluster [%0], [%1, {%3,%4,%5,%6}], [%2], %7;" ::"r"(dst), "l"(m), "r"(bar), "r"(c0), "r"(c1), "r"(c2), "r"(c3), "h"((uint16_t)3) : "memory");
}
__device__ __forceinline__ bool elect() { uint32_t e; asm volatile("{ .reg .pred p; elect.sync _|p, 0xffffffff; selp.u32 %0,1,0,p; }" : "=r"(e)); return e != 0; }
__device__ __forceinline__ void prefetch_tmap(const CUtensorMap* m) { asm volatile("prefetch.tensormap [%0];" ::"l"(m) : "memory"); }
__device__ __forceinline__ void fence_async_smem() { asm volatile("fence.proxy.async.shared::cta;" ::: "memory"); }
__device__ __forceinline__ void fence_async_global() { asm volatile("fence.proxy.async.global;" ::: "memory"); }
__device__ __forceinline__ void wg_fence() { asm volatile("wgmma.fence.sync.aligned;" ::: "memory"); }
__device__ __forceinline__ void wg_commit() { asm volatile("wgmma.commit_group.sync.aligned;" ::: "memory"); }
template <int N> __device__ __forceinline__ void wg_wait() { asm volatile("wgmma.wait_group.sync.aligned %0;" ::"n"(N) : "memory"); }
__device__ __forceinline__ void bar_sync(int id, int n) { asm volatile("bar.sync %0, %1;" ::"r"(id), "r"(n) : "memory"); }
__device__ __forceinline__ uint32_t ld_relaxed(const uint32_t* p) { uint32_t v; asm volatile("ld.relaxed.gpu.global.u32 %0, [%1];" : "=r"(v) : "l"(p) : "memory"); return v; }
__device__ __forceinline__ void st_flag(uint32_t* p, uint32_t v) { asm volatile("st.release.gpu.global.u32 [%0], %1;" ::"l"(p), "r"(v) : "memory"); }
__device__ __forceinline__ unsigned long long ld_relaxed64(const unsigned long long* p) { unsigned long long v; asm volatile("ld.relaxed.gpu.global.u64 %0, [%1];" : "=l"(v) : "l"(p) : "memory"); return v; }
__device__ __forceinline__ void ld_relaxed128(const void* p, unsigned long long& a, unsigned long long& b) { asm volatile("ld.relaxed.gpu.global.v2.u64 {%0,%1}, [%2];" : "=l"(a), "=l"(b) : "l"(p) : "memory"); }
__device__ __forceinline__ void st_relaxed64(unsigned long long* p, unsigned long long v) { asm volatile("st.relaxed.gpu.global.u64 [%0], %1;" ::"l"(p), "l"(v) : "memory"); }
__device__ __forceinline__ void ldsm4(uint32_t addr, uint32_t& a, uint32_t& b, uint32_t& c, uint32_t& d) {
    asm volatile("ldmatrix.sync.aligned.m8n8.x4.shared.b16 {%0,%1,%2,%3}, [%4];" : "=r"(a), "=r"(b), "=r"(c), "=r"(d) : "r"(addr) : "memory");
}
__device__ __forceinline__ void stsm4(uint32_t addr, uint32_t a, uint32_t b, uint32_t c, uint32_t d) {
    asm volatile("stmatrix.sync.aligned.m8n8.x4.shared.b16 [%0], {%1,%2,%3,%4};" ::"r"(addr), "r"(a), "r"(b), "r"(c), "r"(d) : "memory");
}
__device__ __forceinline__ uint4 lds128u(uint32_t addr) { uint4 v; asm volatile("ld.shared.v4.u32 {%0,%1,%2,%3}, [%4];" : "=r"(v.x), "=r"(v.y), "=r"(v.z), "=r"(v.w) : "r"(addr) : "memory"); return v; }
__device__ __forceinline__ uint32_t lds32u(uint32_t addr) { uint32_t v; asm volatile("ld.shared.u32 %0, [%1];" : "=r"(v) : "r"(addr) : "memory"); return v; }
__device__ __forceinline__ void sts32u(uint32_t addr, uint32_t a) { asm volatile("st.shared.u32 [%0], %1;" ::"r"(addr), "r"(a) : "memory"); }
__device__ __forceinline__ uint32_t hfma2(uint32_t a, uint32_t b, uint32_t c) { uint32_t d; asm("fma.rn.bf16x2 %0,%1,%2,%3;" : "=r"(d) : "r"(a), "r"(b), "r"(c)); return d; }
__device__ __forceinline__ float2 lds64(uint32_t addr) { float2 v; asm volatile("ld.shared.v2.f32 {%0,%1}, [%2];" : "=f"(v.x), "=f"(v.y) : "r"(addr) : "memory"); return v; }
__device__ __forceinline__ void sts64(uint32_t addr, float a, float b) { asm volatile("st.shared.v2.f32 [%0], {%1,%2};" ::"r"(addr), "f"(a), "f"(b) : "memory"); }
__device__ __forceinline__ void sts32(uint32_t addr, float a) { asm volatile("st.shared.f32 [%0], %1;" ::"r"(addr), "f"(a) : "memory"); }
__device__ __forceinline__ float lds32(uint32_t addr) { float v; asm volatile("ld.shared.f32 %0, [%1];" : "=f"(v) : "r"(addr) : "memory"); return v; }
__device__ __forceinline__ uint32_t pack2(float lo, float hi) { uint32_t r; asm("cvt.rn.bf16x2.f32 %0, %1, %2;" : "=r"(r) : "f"(hi), "f"(lo)); return r; }
__device__ __forceinline__ float bf_lo(uint32_t v) { return __uint_as_float(v << 16); }
__device__ __forceinline__ float bf_hi(uint32_t v) { return __uint_as_float(v & 0xffff0000u); }
__device__ __forceinline__ float ex2(float x) { float y; asm("ex2.approx.ftz.f32 %0, %1;" : "=f"(y) : "f"(x)); return y; }
__device__ __forceinline__ float tanh_fast(float x) { float y; asm("tanh.approx.f32 %0, %1;" : "=f"(y) : "f"(x)); return y; }
__device__ __forceinline__ uint64_t make_desc(uint32_t addr, uint32_t lbo, uint32_t sbo, uint32_t swz) {
    return (uint64_t)((addr & 0x3FFFF) >> 4) | ((uint64_t)(lbo >> 4) << 16) | ((uint64_t)(sbo >> 4) << 32) | ((uint64_t)swz << 62);
}
template <int N> __device__ __forceinline__ void zero_regs(float (&r)[N]) {
#pragma unroll
    for (int i = 0; i < N; i++) r[i] = 0.f;
}
template <int N> __device__ __forceinline__ void fence_regs(float (&r)[N]) {
#pragma unroll
    for (int i = 0; i < N; i++) asm volatile("" : "+f"(r[i])::"memory");
}

__device__ __forceinline__ void wgmma_rs_n80_tb1(float (&d)[40], uint32_t a0, uint32_t a1, uint32_t a2, uint32_t a3, uint64_t db, int scale_d){
  asm volatile("{ .reg .pred p; setp.ne.b32 p, %45, 0;\n"
   "wgmma.mma_async.sync.aligned.m64n80k16.f32.bf16.bf16 {%0, %1, %2, %3, %4, %5, %6, %7, %8, %9, %10, %11, %12, %13, %14, %15, %16, %17, %18, %19, %20, %21, %22, %23, %24, %25, %26, %27, %28, %29, %30, %31, %32, %33, %34, %35, %36, %37, %38, %39}, {%40, %41, %42, %43}, %44, p, 1, 1, 1; }"
   : "+f"(d[0]), "+f"(d[1]), "+f"(d[2]), "+f"(d[3]), "+f"(d[4]), "+f"(d[5]), "+f"(d[6]), "+f"(d[7]), "+f"(d[8]), "+f"(d[9]), "+f"(d[10]), "+f"(d[11]), "+f"(d[12]), "+f"(d[13]), "+f"(d[14]), "+f"(d[15]), "+f"(d[16]), "+f"(d[17]), "+f"(d[18]), "+f"(d[19]), "+f"(d[20]), "+f"(d[21]), "+f"(d[22]), "+f"(d[23]), "+f"(d[24]), "+f"(d[25]), "+f"(d[26]), "+f"(d[27]), "+f"(d[28]), "+f"(d[29]), "+f"(d[30]), "+f"(d[31]), "+f"(d[32]), "+f"(d[33]), "+f"(d[34]), "+f"(d[35]), "+f"(d[36]), "+f"(d[37]), "+f"(d[38]), "+f"(d[39]) : "r"(a0), "r"(a1), "r"(a2), "r"(a3), "l"(db), "r"(scale_d));
}
__device__ __forceinline__ void wgmma_rs_n64_tb0(float (&d)[32], uint32_t a0, uint32_t a1, uint32_t a2, uint32_t a3, uint64_t db, int scale_d){
  asm volatile("{ .reg .pred p; setp.ne.b32 p, %37, 0;\n"
   "wgmma.mma_async.sync.aligned.m64n64k16.f32.bf16.bf16 {%0, %1, %2, %3, %4, %5, %6, %7, %8, %9, %10, %11, %12, %13, %14, %15, %16, %17, %18, %19, %20, %21, %22, %23, %24, %25, %26, %27, %28, %29, %30, %31}, {%32, %33, %34, %35}, %36, p, 1, 1, 0; }"
   : "+f"(d[0]), "+f"(d[1]), "+f"(d[2]), "+f"(d[3]), "+f"(d[4]), "+f"(d[5]), "+f"(d[6]), "+f"(d[7]), "+f"(d[8]), "+f"(d[9]), "+f"(d[10]), "+f"(d[11]), "+f"(d[12]), "+f"(d[13]), "+f"(d[14]), "+f"(d[15]), "+f"(d[16]), "+f"(d[17]), "+f"(d[18]), "+f"(d[19]), "+f"(d[20]), "+f"(d[21]), "+f"(d[22]), "+f"(d[23]), "+f"(d[24]), "+f"(d[25]), "+f"(d[26]), "+f"(d[27]), "+f"(d[28]), "+f"(d[29]), "+f"(d[30]), "+f"(d[31]) : "r"(a0), "r"(a1), "r"(a2), "r"(a3), "l"(db), "r"(scale_d));
}
__device__ __forceinline__ void wgmma_rs_n24_tb1(float (&d)[12], uint32_t a0, uint32_t a1, uint32_t a2, uint32_t a3, uint64_t db, int scale_d){
  asm volatile("{ .reg .pred p; setp.ne.b32 p, %17, 0;\n"
   "wgmma.mma_async.sync.aligned.m64n24k16.f32.bf16.bf16 {%0, %1, %2, %3, %4, %5, %6, %7, %8, %9, %10, %11}, {%12, %13, %14, %15}, %16, p, 1, 1, 1; }"
   : "+f"(d[0]), "+f"(d[1]), "+f"(d[2]), "+f"(d[3]), "+f"(d[4]), "+f"(d[5]), "+f"(d[6]), "+f"(d[7]), "+f"(d[8]), "+f"(d[9]), "+f"(d[10]), "+f"(d[11]) : "r"(a0), "r"(a1), "r"(a2), "r"(a3), "l"(db), "r"(scale_d));
}
__device__ __forceinline__ void wgmma_ss_n80_tb1(float (&d)[40], uint64_t da, uint64_t db, int scale_d){
  asm volatile("{ .reg .pred p; setp.ne.b32 p, %42, 0;\n"
   "wgmma.mma_async.sync.aligned.m64n80k16.f32.bf16.bf16 {%0, %1, %2, %3, %4, %5, %6, %7, %8, %9, %10, %11, %12, %13, %14, %15, %16, %17, %18, %19, %20, %21, %22, %23, %24, %25, %26, %27, %28, %29, %30, %31, %32, %33, %34, %35, %36, %37, %38, %39}, %40, %41, p, 1, 1, 0, 1; }"
   : "+f"(d[0]), "+f"(d[1]), "+f"(d[2]), "+f"(d[3]), "+f"(d[4]), "+f"(d[5]), "+f"(d[6]), "+f"(d[7]), "+f"(d[8]), "+f"(d[9]), "+f"(d[10]), "+f"(d[11]), "+f"(d[12]), "+f"(d[13]), "+f"(d[14]), "+f"(d[15]), "+f"(d[16]), "+f"(d[17]), "+f"(d[18]), "+f"(d[19]), "+f"(d[20]), "+f"(d[21]), "+f"(d[22]), "+f"(d[23]), "+f"(d[24]), "+f"(d[25]), "+f"(d[26]), "+f"(d[27]), "+f"(d[28]), "+f"(d[29]), "+f"(d[30]), "+f"(d[31]), "+f"(d[32]), "+f"(d[33]), "+f"(d[34]), "+f"(d[35]), "+f"(d[36]), "+f"(d[37]), "+f"(d[38]), "+f"(d[39]) : "l"(da), "l"(db), "r"(scale_d));
}
__device__ __forceinline__ void wgmma_ss_n64_tb1(float (&d)[32], uint64_t da, uint64_t db, int scale_d){
  asm volatile("{ .reg .pred p; setp.ne.b32 p, %34, 0;\n"
   "wgmma.mma_async.sync.aligned.m64n64k16.f32.bf16.bf16 {%0, %1, %2, %3, %4, %5, %6, %7, %8, %9, %10, %11, %12, %13, %14, %15, %16, %17, %18, %19, %20, %21, %22, %23, %24, %25, %26, %27, %28, %29, %30, %31}, %32, %33, p, 1, 1, 0, 1; }"
   : "+f"(d[0]), "+f"(d[1]), "+f"(d[2]), "+f"(d[3]), "+f"(d[4]), "+f"(d[5]), "+f"(d[6]), "+f"(d[7]), "+f"(d[8]), "+f"(d[9]), "+f"(d[10]), "+f"(d[11]), "+f"(d[12]), "+f"(d[13]), "+f"(d[14]), "+f"(d[15]), "+f"(d[16]), "+f"(d[17]), "+f"(d[18]), "+f"(d[19]), "+f"(d[20]), "+f"(d[21]), "+f"(d[22]), "+f"(d[23]), "+f"(d[24]), "+f"(d[25]), "+f"(d[26]), "+f"(d[27]), "+f"(d[28]), "+f"(d[29]), "+f"(d[30]), "+f"(d[31]) : "l"(da), "l"(db), "r"(scale_d));
}
__device__ __forceinline__ void wgmma_rs_n64_tb1(float (&d)[32], uint32_t a0, uint32_t a1, uint32_t a2, uint32_t a3, uint64_t db, int scale_d){
  asm volatile("{ .reg .pred p; setp.ne.b32 p, %37, 0;\n"
   "wgmma.mma_async.sync.aligned.m64n64k16.f32.bf16.bf16 {%0, %1, %2, %3, %4, %5, %6, %7, %8, %9, %10, %11, %12, %13, %14, %15, %16, %17, %18, %19, %20, %21, %22, %23, %24, %25, %26, %27, %28, %29, %30, %31}, {%32, %33, %34, %35}, %36, p, 1, 1, 1; }"
   : "+f"(d[0]), "+f"(d[1]), "+f"(d[2]), "+f"(d[3]), "+f"(d[4]), "+f"(d[5]), "+f"(d[6]), "+f"(d[7]), "+f"(d[8]), "+f"(d[9]), "+f"(d[10]), "+f"(d[11]), "+f"(d[12]), "+f"(d[13]), "+f"(d[14]), "+f"(d[15]), "+f"(d[16]), "+f"(d[17]), "+f"(d[18]), "+f"(d[19]), "+f"(d[20]), "+f"(d[21]), "+f"(d[22]), "+f"(d[23]), "+f"(d[24]), "+f"(d[25]), "+f"(d[26]), "+f"(d[27]), "+f"(d[28]), "+f"(d[29]), "+f"(d[30]), "+f"(d[31]) : "r"(a0), "r"(a1), "r"(a2), "r"(a3), "l"(db), "r"(scale_d));
}
__device__ __forceinline__ void wgmma_zero_n64(float (&d)[32], const uint32_t (&z)[4], uint64_t db){
  asm volatile("{ .reg .pred p; setp.ne.b32 p, 0, 0;\n"
   "wgmma.mma_async.sync.aligned.m64n64k16.f32.bf16.bf16 {%0, %1, %2, %3, %4, %5, %6, %7, %8, %9, %10, %11, %12, %13, %14, %15, %16, %17, %18, %19, %20, %21, %22, %23, %24, %25, %26, %27, %28, %29, %30, %31}, {%32, %33, %34, %35}, %36, p, 1, 1, 0; }"
   : "=f"(d[0]), "=f"(d[1]), "=f"(d[2]), "=f"(d[3]), "=f"(d[4]), "=f"(d[5]), "=f"(d[6]), "=f"(d[7]), "=f"(d[8]), "=f"(d[9]), "=f"(d[10]), "=f"(d[11]), "=f"(d[12]), "=f"(d[13]), "=f"(d[14]), "=f"(d[15]), "=f"(d[16]), "=f"(d[17]), "=f"(d[18]), "=f"(d[19]), "=f"(d[20]), "=f"(d[21]), "=f"(d[22]), "=f"(d[23]), "=f"(d[24]), "=f"(d[25]), "=f"(d[26]), "=f"(d[27]), "=f"(d[28]), "=f"(d[29]), "=f"(d[30]), "=f"(d[31]) : "r"(z[0]), "r"(z[1]), "r"(z[2]), "r"(z[3]), "l"(db));
}
__device__ __forceinline__ void wgmma_zero_n80(float (&d)[40], const uint32_t (&z)[4], uint64_t db){
  asm volatile("{ .reg .pred p; setp.ne.b32 p, 0, 0;\n"
   "wgmma.mma_async.sync.aligned.m64n80k16.f32.bf16.bf16 {%0, %1, %2, %3, %4, %5, %6, %7, %8, %9, %10, %11, %12, %13, %14, %15, %16, %17, %18, %19, %20, %21, %22, %23, %24, %25, %26, %27, %28, %29, %30, %31, %32, %33, %34, %35, %36, %37, %38, %39}, {%40, %41, %42, %43}, %44, p, 1, 1, 0; }"
   : "=f"(d[0]), "=f"(d[1]), "=f"(d[2]), "=f"(d[3]), "=f"(d[4]), "=f"(d[5]), "=f"(d[6]), "=f"(d[7]), "=f"(d[8]), "=f"(d[9]), "=f"(d[10]), "=f"(d[11]), "=f"(d[12]), "=f"(d[13]), "=f"(d[14]), "=f"(d[15]), "=f"(d[16]), "=f"(d[17]), "=f"(d[18]), "=f"(d[19]), "=f"(d[20]), "=f"(d[21]), "=f"(d[22]), "=f"(d[23]), "=f"(d[24]), "=f"(d[25]), "=f"(d[26]), "=f"(d[27]), "=f"(d[28]), "=f"(d[29]), "=f"(d[30]), "=f"(d[31]), "=f"(d[32]), "=f"(d[33]), "=f"(d[34]), "=f"(d[35]), "=f"(d[36]), "=f"(d[37]), "=f"(d[38]), "=f"(d[39]) : "r"(z[0]), "r"(z[1]), "r"(z[2]), "r"(z[3]), "l"(db));
}


struct Params {
    const bf16 *x, *wqkv, *wo, *wg, *wu, *wd, *c, *wmod;
    bf16* out;
};

__device__ __forceinline__ float rcp_fast(float x) { float y; asm("rcp.approx.ftz.f32 %0, %1;" : "=f"(y) : "f"(x)); return y; }
__device__ __forceinline__ float silu_bf(bf16 c) {
    float f = __bfloat162float(c);
    float s = __fdividef(f, 1.f + __expf(-f));
    return __bfloat162float(__float2bfloat16(s));
}
__device__ __forceinline__ void fma8(float (&a)[8], uint4 w, float s) {
    a[0] = fmaf(bf_lo(w.x), s, a[0]); a[1] = fmaf(bf_hi(w.x), s, a[1]);
    a[2] = fmaf(bf_lo(w.y), s, a[2]); a[3] = fmaf(bf_hi(w.y), s, a[3]);
    a[4] = fmaf(bf_lo(w.z), s, a[4]); a[5] = fmaf(bf_hi(w.z), s, a[5]);
    a[6] = fmaf(bf_lo(w.w), s, a[6]); a[7] = fmaf(bf_hi(w.w), s, a[7]);
}
__device__ __forceinline__ float reduce8(float (&a)[8], int lane) {
    const bool b4 = lane & 16, b3 = lane & 8, b2 = lane & 4;
    float h[4];
#pragma unroll
    for (int i = 0; i < 4; i++) { float send = b4 ? a[i] : a[i + 4]; float keep = b4 ? a[i + 4] : a[i]; h[i] = keep + __shfl_xor_sync(~0u, send, 16); }
    float q[2];
#pragma unroll
    for (int i = 0; i < 2; i++) { float send = b3 ? h[i] : h[i + 2]; float keep = b3 ? h[i + 2] : h[i]; q[i] = keep + __shfl_xor_sync(~0u, send, 8); }
    float send = b2 ? q[0] : q[1], keep = b2 ? q[1] : q[0];
    float r = keep + __shfl_xor_sync(~0u, send, 4);
    r += __shfl_xor_sync(~0u, r, 2);
    return r;
}

struct LnRow { uint32_t rs, rl, nm; };
template <bool LO> __device__ __forceinline__ uint32_t ln_one(uint32_t r, const LnRow& k, uint32_t c, uint32_t sh) {
    const uint32_t d = hfma2(r, 0x3f803f80u, k.nm);
    return hfma2(hfma2(d, k.rs, LO ? hfma2(d, k.rl, 0x80008000u) : 0x80008000u), c, sh);
}
template <bool LO>
__device__ __forceinline__ void ln_frag(uint32_t (&a)[4], uint32_t r0, uint32_t r1, uint32_t r2, uint32_t r3, uint4 M, const LnRow& k0, const LnRow& k1) {
    a[0] = ln_one<LO>(r0, k0, M.x, M.z); a[1] = ln_one<LO>(r1, k1, M.x, M.z);
    a[2] = ln_one<LO>(r2, k0, M.y, M.w); a[3] = ln_one<LO>(r3, k1, M.y, M.w);
}
__device__ __forceinline__ float rbf(float v) { return bf_lo(pack2(v, 0.f)); }
__device__ __forceinline__ LnRow ln_consts(float mean, float var) {
    float sd; asm("sqrt.approx.ftz.f32 %0, %1;" : "=f"(sd) : "f"(rbf(rbf(var) + 1e-5f)));
    const float inv = rcp_fast(rbf(sd));
    const float hi = rbf(inv), lo = inv - hi, nm = -mean;
    LnRow k; k.rs = pack2(hi, hi); k.rl = pack2(lo, lo); k.nm = pack2(nm, nm);
    return k;
}

template <int H>
__device__ __forceinline__ void qk_mma(float (&s)[32], const uint32_t (&q)[32], uint32_t kv, uint32_t ones) {
    constexpr int P = H >> 1, ODD = H & 1;
    const uint32_t* qq = q + H * 8;
    const uint32_t mid = kv + (P * 5 + 2) * 1024;
    const uint32_t q4[4] = {qq[0], qq[1], qq[2], qq[3]};
    wgmma_zero_n64(s, q4, make_desc(kv + (P * 5 + (ODD ? 3 : 0)) * 1024, 1024, 128, 0));
    wgmma_rs_n64_tb0(s, qq[4], qq[5], qq[6], qq[7], make_desc(mid, ones - mid, 128, 0), 1);
}
__device__ __forceinline__ void mask_s(float (&s)[32], int mm, int wr, int dg) {
    if (mm) {
        const bool causal = mm == 1;
        const bool k0 = (dg <= 0) == causal, k1 = (dg + 1 <= 0) == causal;
#pragma unroll
        for (int kg = 0; kg < 4; kg++) {
            float* v = s + kg * 8;
            const bool diag = kg == wr, live = (kg < wr) == causal;
            const bool a = diag ? k0 : live, b = diag ? k1 : live, c = diag ? causal : live, d = diag ? !causal : live;
            v[0] = a ? v[0] : -INFINITY; v[1] = b ? v[1] : -INFINITY; v[6] = a ? v[6] : -INFINITY; v[7] = b ? v[7] : -INFINITY;
            v[2] = c ? v[2] : -INFINITY; v[3] = c ? v[3] : -INFINITY; v[4] = d ? v[4] : -INFINITY; v[5] = d ? v[5] : -INFINITY;
        }
    }
}
__device__ __forceinline__ void row_max(const float (&s)[32], float& m0, float& m1, float& a0, float& a1) {
    float x0 = fmaxf(s[0], s[1]), x1 = fmaxf(s[2], s[3]), y0 = fmaxf(s[4], s[5]), y1 = fmaxf(s[6], s[7]);
#pragma unroll
    for (int nb = 2; nb < 8; nb += 2) {
        x0 = fmaxf(x0, fmaxf(s[nb * 4], s[nb * 4 + 1])); x1 = fmaxf(x1, fmaxf(s[nb * 4 + 2], s[nb * 4 + 3]));
        y0 = fmaxf(y0, fmaxf(s[nb * 4 + 4], s[nb * 4 + 5])); y1 = fmaxf(y1, fmaxf(s[nb * 4 + 6], s[nb * 4 + 7]));
    }
    x0 = fmaxf(fmaxf(x0, y0), m0); x1 = fmaxf(fmaxf(x1, y1), m1);
    x0 = fmaxf(x0, __shfl_xor_sync(~0u, x0, 1)); x1 = fmaxf(x1, __shfl_xor_sync(~0u, x1, 1));
    x0 = fmaxf(x0, __shfl_xor_sync(~0u, x0, 2)); x1 = fmaxf(x1, __shfl_xor_sync(~0u, x1, 2));
    a0 = ex2(m0 - x0); a1 = ex2(m1 - x1);
    m0 = x0; m1 = x1;
}
__device__ __forceinline__ void pv_mma(float (&o)[12], const uint32_t (&p)[16], uint32_t vaddr) {
    uint64_t dv = make_desc(vaddr, 128, 1024, 0);
#pragma unroll
    for (int kg = 0; kg < 4; kg++) wgmma_rs_n24_tb1(o, p[kg * 4], p[kg * 4 + 1], p[kg * 4 + 2], p[kg * 4 + 3], dv + kg * 16, 1);
}
template <int H>
__device__ __forceinline__ void att_fast(float (&cur)[32], float (&nxt)[32], uint32_t (&p)[16], const uint32_t (&pprev)[16], float (&oprev)[12],
                                         const uint32_t (&q)[32], uint32_t kvprev, uint32_t kvnext, uint32_t ones, int mm, const uint32_t (&mk)[9]) {
    wg_fence();
    qk_mma<(H + 1) & 3>(nxt, q, kvnext, ones);
    pv_mma(oprev, pprev, kvprev + (10 + 3 * ((H + 3) & 3)) * 1024);
    wg_commit();
#pragma unroll
    for (int i = 0; i < 16; i++) p[i] = pack2(ex2(cur[2 * i]), ex2(cur[2 * i + 1]));
#pragma unroll
    for (int i = 0; i < 16; i++) asm volatile("" : "+r"(p[i]));
    wg_wait<0>();
    fence_regs(nxt);
    if (mm) {
#pragma unroll
        for (int kg = 0; kg < 4; kg++) { p[kg * 4] &= mk[kg]; p[kg * 4 + 3] &= mk[kg]; p[kg * 4 + 1] &= mk[4 + kg]; p[kg * 4 + 2] &= mk[5 + kg]; }
    }
#pragma unroll
    for (int i = 0; i < 16; i++) asm volatile("" : "+r"(p[i]));
}

__global__ void __cluster_dims__(2, 1, 1) __launch_bounds__(384, 1)
fused_block_kernel(const __grid_constant__ CUtensorMap tm_x, const __grid_constant__ CUtensorMap tm_qm, const __grid_constant__ CUtensorMap tm_qr,
                   const __grid_constant__ CUtensorMap tm_om, const __grid_constant__ CUtensorMap tm_g,
                   const __grid_constant__ CUtensorMap tm_u, const __grid_constant__ CUtensorMap tm_dm,
                   const __grid_constant__ CUtensorMap tm_m, const __grid_constant__ CUtensorMap tm_xt, const __grid_constant__ CUtensorMap tm_out,
                   const __grid_constant__ CUtensorMap tm_g1, const __grid_constant__ CUtensorMap tm_u1,
                   const Params prm) {
    extern __shared__ __align__(1024) uint8_t smem[];
    const uint32_t sb = smem_u32(smem);
    const uint32_t bars = sb + SM_BAR;
#define BAR(i) (bars + 8u * (uint32_t)(i))
    const int tid = threadIdx.x, warp = tid >> 5, lane = tid & 31;
    const int bid = blockIdx.x;
    const uint32_t rank = bid & 1;
    const int uslice = (bid >> 1) + rank * 64;
    auto read_info = [&](int& j, int& rb, uint32_t& tag) {
        asm volatile("barrier.cluster.wait.aligned;" ::: "memory");
        uint32_t v0, v1;
        asm volatile("{ .reg .b32 ra; mapa.shared::cluster.u32 ra, %2, 0; ld.shared::cluster.v2.u32 {%0,%1}, [ra]; }" : "=r"(v0), "=r"(v1) : "r"(sb + SM_INFO) : "memory");
        v0 = __shfl_sync(~0u, v0, 0); v1 = __shfl_sync(~0u, v1, 0);
        j = v0 & 7; rb = (v0 >> 3) * 2 + rank; tag = v1;
    };

    if (warp >= 8) {
        asm volatile("setmaxnreg.dec.sync.aligned.u32 40;");
        const int pw = __shfl_sync(~0u, warp - 8, 0);
        const bool el = elect();
        if (el) {
            if (pw == 0) {
                mbar_init(BAR(B_M0), 1); mbar_init(BAR(B_C), 1); mbar_init(BAR(B_XR), 1); mbar_init(BAR(B_M0B), 1);
                asm volatile("fence.mbarrier_init.release.cluster;" ::: "memory");
                mbar_expect_tx(BAR(B_C), 1280);
                bulk_load(sb + SM_P0 + 40960, prm.c, 1280, BAR(B_C));
                if (uslice < 80) {
                    mbar_expect_tx(BAR(B_M0), 10240); mbar_expect_tx(BAR(B_M0B), 10240);
#pragma unroll
                    for (int u = 0; u < 4; u++) tma2d(sb + SM_P0 + u * 5120, &tm_m, uslice * 16, u * 160, u < 2 ? BAR(B_M0) : BAR(B_M0B));
                }
                mbar_expect_tx(BAR(B_XR), 20480);
                bulk_load(sb + SM_P0 + 20480, prm.x + (size_t)bid * 16 * DM, 20480, BAR(B_XR));
                prefetch_tmap(&tm_x); prefetch_tmap(&tm_qm); prefetch_tmap(&tm_qr);
            } else if (pw == 1) {
                if (rank == 0) {
                    uint32_t smid; asm volatile("mov.u32 %0, %%smid;" : "=r"(smid));
                    const uint32_t tp = smid >> 1;
                    uint32_t pref;
                    if (tp < 32) pref = (tp & 7) * 8 + (tp >> 3);
                    else if (tp < 60) pref = (1 + (tp - 32) % 7) * 8 + 4 + (tp - 32) / 7;
                    else pref = (tp - 58) & 7;
                    const uint32_t old = atomicAdd(&g_slot[pref], 1u);
                    const uint32_t ep = ld_relaxed(&g_done) >> 7;
                    if (((old ^ ep) & 0x1ffffffu) != 0) {
                        atomicAdd(&g_slot[pref], 0xffffffffu);
                        const uint32_t full = (old & ~0x1ffffffu) | ep;
#pragma unroll 1
                        for (int k = 1; k < 64; k++) {
                            uint32_t sl = (pref + k) & 63;
                            if (atomicCAS(&g_slot[sl], full, full + 1) == full) { pref = sl; break; }
                        }
                    }
                    asm volatile("st.shared.v2.u32 [%0], {%1,%2};" ::"r"(sb + SM_INFO), "r"(pref), "r"(ep + 1) : "memory");
                    asm volatile("fence.release.sync_restrict::shared::cta.cluster;" ::: "memory");
                }
            } else if (pw == 2) {
#pragma unroll
                for (int i = 0; i < 49; i++) mbar_init(BAR(i), bar_count(i));
                asm volatile("fence.mbarrier_init.release.cluster;" ::: "memory");
            } else {
#pragma unroll
                for (int i = 49; i < B_M0; i++) mbar_init(BAR(i), bar_count(i));
                asm volatile("fence.mbarrier_init.release.cluster;" ::: "memory");
            }
        }
        __syncwarp();
        asm volatile("barrier.cluster.arrive.relaxed.aligned;" ::: "memory");
        int j, rb; uint32_t tag;
        read_info(j, rb, tag);
        const int cm = 80 * j, cr = 80 * j + 64;
        if (pw == 0) {
            if (el) {
                mbar_wait_long(BAR(B_XR), 0);
                if (uslice < 80) mbar_wait_long(BAR(B_M0B), 0);
                l2_prefetch((const uint8_t*)prm.wqkv + (size_t)bid * 19200, 19200);
#pragma unroll 1
                for (int s = 0; s < 10; s++) {
                    const int slot = s & 3;
                    if (s == 2) mbar_wait(BAR(B_MC), 0);
                    if (s >= 4) mbar_wait(BAR(B_PE + slot), ((s >> 2) & 1) ^ 1);
                    mbar_expect_tx(BAR(B_PF + slot), 30720);
                    uint32_t dst = sb + slot * P1_STAGE + 16384 + rank * 18432;
                    tma4d_mc(dst, &tm_qm, cm, 64 * s + 32 * rank, 0, 0, BAR(B_PF + slot));
                    tma3d_mc(dst + 12288, &tm_qr, cr, 64 * s + 32 * rank, 0, BAR(B_PF + slot));
                }
                prefetch_tmap(&tm_om); prefetch_tmap(&tm_g); prefetch_tmap(&tm_u); prefetch_tmap(&tm_dm); prefetch_tmap(&tm_xt); prefetch_tmap(&tm_out); prefetch_tmap(rank ? &tm_u1 : &tm_g1);
                mbar_wait_long(BAR(B_PD + 0), 0);
#pragma unroll 1
                for (int h = 0; h < 2; h++) {
                    const int slice = h == 0 ? 80 + bid : (rank ? 208 + (bid >> 1) : 240);
                    if (slice < 240) {
                        mbar_expect_tx(BAR(B_M1 + h), 20480);
#pragma unroll
                        for (int u = 0; u < 4; u++) tma2d(sb + SM_NS + h * 20480 + u * 5120, &tm_m, slice * 16, u * 160, BAR(B_M1 + h));
                    }
                }
                {
                    mbar_wait_long(BAR(B_KVS), 0);
                    const int nt = bid < 64 ? 2 : 1;
                    mbar_expect_tx(BAR(B_RP), nt * 10240);
#pragma unroll 1
                    for (int h = 0; h < nt; h++) {
                        const int tile = bid + h * 128, tj = tile / 24, ts = tile - tj * 24;
                        tma3d(sb + h * 10240, &tm_dm, 80 * tj, 192 * (ts & 7) + 64 * (ts >> 3), 0, BAR(B_RP));
                    }
                    mbar_wait_long(BAR(B_RP), 0);
#pragma unroll 1
                    for (int h = 0; h < nt; h++) bulk_store(g_wd + (size_t)(bid + h * 128) * 10240, sb + h * 10240, 10240);
                    bulk_commit_wait();
                    mbar_arrive_cta(BAR(B_NS), 0); mbar_arrive_cta(BAR(B_NS), 1);
                    asm volatile("fence.acq_rel.gpu;" ::: "memory");
#pragma unroll 1
                    for (int h = 0; h < nt; h++) {
                        const int tile = bid + h * 128, tj = tile / 24;
                        asm volatile("st.relaxed.gpu.global.u32 [%0], %1;" ::"l"(&g_wdflag[tj][tile - tj * 24]), "r"(tag) : "memory");
                    }
                }
                mbar_wait_long(BAR(B_NS), 0);
#pragma unroll 1
                for (int st = 0; st < 8; st++) {
                    if (st == 6) {
                        const unsigned long long tt = ((unsigned long long)tag << 32) | tag;
#pragma unroll 1
                        for (int u = 0; u < 2; u++) {
                            unsigned long long v[6];
#pragma unroll 1
                            for (int n = 0; n < SPIN_LIMIT; n++) {
#pragma unroll
                                for (int e = 0; e < 3; e++) ld_relaxed128(&g_wdflag[j][u * 12 + e * 4], v[2 * e], v[2 * e + 1]);
                                if (v[0] == tt && v[1] == tt && v[2] == tt && v[3] == tt && v[4] == tt && v[5] == tt) break;
                            }
                        }
                        asm volatile("fence.acquire.gpu;" ::: "memory");
                        fence_async_global();
                    }
                    if (st == 6) mbar_wait_long(BAR(B_PD + 1), 0);
                    const int jj = st == 0 ? j : (st - 1 < j ? st - 1 : st);
                    mbar_expect_tx(BAR(B_WOF + st), 12800);
                    if ((uint32_t)(st & 1) == rank) tma3d_mc(sb + SM_WO + st * WO_SL, &tm_om, 80 * j, 80 * jj, 0, BAR(B_WOF + st));
                }
                mbar_wait(BAR(B_PD + 2), 0);
                int slot = 0; uint32_t ph = 1;
#pragma unroll 1
                for (int s = 0; s < 22; s++) {
                    if (s == 2) mbar_wait_long(BAR(B_G), 0);
                    mbar_wait(BAR(B_BE + slot), ph);
                    const uint32_t dst = sb + b4_off(slot);
                    if (s < 10) {
                        mbar_expect_tx(BAR(B_BF + slot), 24576);
#pragma unroll
                        for (int h = 0; h < 2; h++) {
                            const int kk = 2 * s + h, st = kk / 5, jj = st == 0 ? j : (st - 1 < j ? st - 1 : st);
                            tma3d_mc(dst + h * 12288 + rank * 6144, rank ? &tm_u : &tm_g, 0, 80 * jj + 16 * (kk - st * 5), 3 * j, BAR(B_BF + slot));
                        }
                    } else {
                        const int st = 4 + ((s - 10) & 3), jj = st - 1 < j ? st - 1 : st;
                        mbar_expect_tx(BAR(B_BF + slot), 20480);
                        tma3d_mc(dst + rank * 10240, rank ? &tm_u1 : &tm_g1, 0, 80 * jj, 3 * j + ((s - 10) >> 2), BAR(B_BF + slot));
                    }
                    if (++slot == 5) { slot = 0; ph ^= 1; }
                }
                mbar_wait(BAR(B_BE + slot), ph);
                const uint8_t* srcb = g_wd + (size_t)j * 24 * 10240;
#pragma unroll 1
                for (int s = rank; s < 4; s += 2) bulk_load_mc(sb + db_off(s), srcb + s * 10240, 10240, BAR(B_DF + s));
                slot = 0; ph = 0;
                const uint8_t* srca = g_hh + (size_t)rb * 24 * 16384;
#pragma unroll 1
                for (int s = 0; s < 24; s++) {
                    if ((s & 7) == 0 || s == 2) { mbar_wait(BAR(B_HQ + (s == 0 ? 0 : 1 + (s >> 3))), 0); fence_async_global(); }
                    mbar_wait(BAR(B_DE + slot), ph);
                    mbar_expect_tx(BAR(B_DF + slot), 16384 + 10240);
                    bulk_load(sb + da_off(slot), srca + ((s & 7) * 3 + (s >> 3)) * 16384, 16384, BAR(B_DF + slot));
                    if (s >= 4 && (uint32_t)(s & 1) == rank) bulk_load_mc(sb + db_off(slot), srcb + s * 10240, 10240, BAR(B_DF + slot));
                    if (++slot == D_NST) { slot = 0; ph ^= 1; }
                }
            }
        } else if (pw == 1) {
            if (el) {
                mbar_wait_long(BAR(B_XR), 0);
                if (uslice < 80) mbar_wait_long(BAR(B_M0B), 0);
#pragma unroll 1
                for (int s = 0; s < 10; s++) {
                    const int slot = s & 3;
                    if (s == 2) mbar_wait(BAR(B_MC), 0);
                    if (s >= 4) mbar_wait(BAR(B_PE + slot), ((s >> 2) & 1) ^ 1);
                    mbar_expect_tx(BAR(B_PF + slot), 16384);
                    tma2d(sb + slot * P1_STAGE, &tm_x, 64 * s, 128 * rb, BAR(B_PF + slot));
                    if (s == 9) mbar_arrive(BAR(B_GO));
                }
            }
            __syncwarp();
            const int R0 = 2 * rb;
            uint32_t fv = 0;
            auto wait_flags = [&](const uint32_t* fp, uint32_t need, uint32_t q) {
                const uint32_t want = (tag << 2) + q;
                if ((__ballot_sync(~0u, fv - want <= 3u - q) & need) != need) {
#pragma unroll 1
                    for (int n = 0; n < SPIN_LIMIT; n++) {
                        fv = ld_relaxed(fp);
                        if ((__ballot_sync(~0u, fv - want <= 3u - q) & need) == need) break;
                    }
                    asm volatile("fence.acquire.gpu;" ::: "memory");
                    __syncwarp();
                    fence_async_global();
                }
            };
            {
                if (el) {
                    if (rb >= 2) { mbar_expect_tx(BAR(B_KVF + 0), KV_BYTES); mbar_expect_tx(BAR(B_KVF + 1), KV_BYTES); }
                    if (rb >= 1) { mbar_expect_tx(BAR(B_KVF + 2), KV_BYTES); mbar_expect_tx(BAR(B_KVF + 3), KV_BYTES); }
                }
                if (rb >= 2 && rank == 0) {
                    const uint32_t* fp = &g_flag[EV_KV][R0 - 1 - (lane & 3)][j];
                    mbar_wait_long(BAR(B_PD + 0), 0);
#pragma unroll 1
                    for (int n = 0; n < 4; n++) {
                        wait_flags(fp, 1u << n, 0);
                        if (el) {
                            const uint8_t* src = g_kv + (size_t)((R0 - 1 - n) * 8 + j) * KV_BYTES;
                            if (n < 2) bulk_load_mc(sb + SM_KV + (2 + n) * KV_BYTES, src, KV_BYTES, BAR(B_KVF + n));
                            else bulk_load(sb + SM_KV + (2 + n) * KV_BYTES, src, KV_BYTES, BAR(B_KVF + n));
                        }
                    }
                }
            }
            mbar_wait_long(BAR(B_NSL), 0);
            {
                constexpr int SC0 = 76800, SC1 = SM_ONES + 1024;
#pragma unroll 1
                for (int n = 0; n < SPIN_LIMIT; n++) {
                    if (el) {
                        mbar_expect_tx(BAR(B_TB), 5760);
                        bulk_load(sb + SC0, &g_mod[960], 5120, BAR(B_TB));
                        bulk_load(sb + SC1, &g_mod[640 + 40 * j], 320, BAR(B_TB));
                        bulk_load(sb + SC1 + 320, &g_mod[1600 + 40 * j], 320, BAR(B_TB));
                    }
                    mbar_wait(BAR(B_TB), n & 1);
                    bool ok = true;
#pragma unroll 1
                    for (int it = lane; it < 360; it += 32) {
                        uint4 v = lds128u(it < 320 ? sb + SC0 + it * 16 : sb + SC1 + (it - 320) * 16);
                        ok = ok && v.y == tag && v.w == tag;
                        if (it < 320) {
                            const int sc = it >= 160, q = it - sc * 160, w = (2 * q) & 7;
                            if (sc) { v.x = hfma2(v.x, 0x3f803f80u, 0x3f803f80u); v.z = hfma2(v.z, 0x3f803f80u, 0x3f803f80u); }
                            const uint32_t a0 = sb + SM_MOD2 + ((q >> 2) * 4 + (w & 3)) * 16 + (w >> 2) * 4 + (sc ? 0 : 8);
                            sts32u(a0, v.x); sts32u(a0 + 16, v.z);
                        } else {
                            if (it >= 340) { v.x = hfma2(v.x, 0x3f003f00u, 0x80008000u); v.z = hfma2(v.z, 0x3f003f00u, 0x80008000u); }
                            sts32u(sb + SM_GV + (it - 320) * 8, v.x); sts32u(sb + SM_GV + (it - 320) * 8 + 4, v.z);
                        }
                    }
                    if (__all_sync(~0u, ok)) break;
                    fence_async_smem();
                    __syncwarp();
                }
            }
            __syncwarp();
            if (el) mbar_arrive(BAR(B_MODS));
            const int foff = (R0 + ((lane >> 3) & 1)) * 32 + (lane & 7);
            fv = 0;
            mbar_wait_long(BAR(B_PUB + 1), 0);
            if (lane < 2) mbar_arrive_cta(BAR(B_PD + 1), lane);
            if (el) { mbar_expect_tx(BAR(B_XT), 20480); tma2d(sb + SM_XT, &tm_xt, 80 * j, 128 * rb, BAR(B_XT)); }
#pragma unroll 1
            for (int st = 1; st < 8; st++) {
                const int jj = st - 1 < j ? st - 1 : st, slot = (0x21403210 >> (4 * st)) & 7;
                if (st >= 4) mbar_wait(BAR(B_TE + (slot == 4 ? 3 : slot)), 0);
                wait_flags(&g_flag[EV_O][0][0] + foff, 0x101u << jj, 0);
                if (el) {
                    const uint32_t fb = slot == 4 ? BAR(B_XT) : BAR(B_TF + slot);
                    mbar_expect_tx(fb, 2 * O_BYTES);
                    bulk_load(sb + SM_T + slot * 20480, g_o + (size_t)(rb * 8 + jj) * (2 * O_BYTES), 2 * O_BYTES, fb);
                }
            }
            fv = 0;
            mbar_wait_long(BAR(B_X1S), 0);
#pragma unroll 1
            for (int st = 1; st < 8; st++) {
                const int jj = st - 1 < j ? st - 1 : st, slot = st & 3;
                if (st >= 4) mbar_wait_long(BAR(B_AE + slot), 0);
                wait_flags(&g_flag[EV_X1][0][0] + foff, (0x101u << jj) | (st == 4 ? 0x101u << j : 0u), st >= 4 ? 1 : 0);
                if (el) {
                    mbar_expect_tx(BAR(B_AF + slot), 2 * O_BYTES);
                    bulk_load(sb + SM_A4 + slot * 20480, (st >= 4 ? g_h2 : g_x1) + (size_t)(rb * 8 + jj) * (2 * O_BYTES), 2 * O_BYTES, BAR(B_AF + slot));
                }
            }
            fv = 0;
#pragma unroll 1
            for (int it = 0; it < 4; it++) {
                if (it == 0) mbar_wait_long(BAR(B_PUB + 3), 0);
                wait_flags(&g_flag[EV_HH][R0][lane & 7], it == 0 ? 0x3u : 0xffu, it ? it - 1 : 0);
                __syncwarp();
                if (el) mbar_arrive(BAR(B_HQ + it));
            }
            if (el) {
                mbar_wait(BAR(B_PD + 3), 0);
                mbar_expect_tx(BAR(B_X1), 20480);
                bulk_load(sb + SM_X1, g_x1 + (size_t)(rb * 8 + j) * (2 * O_BYTES), 2 * O_BYTES, BAR(B_X1));
                prefetch_tmap(&tm_out);
            }
        } else {
            const int hw = pw - 2;
            const int R = 2 * rb + hw;
            if (el) {
                mbar_wait_long(BAR(B_GO), 0);
                if (hw == 1) atomicAdd(&g_done, 1u);
                if (hw == 0) {
#pragma unroll 1
                    for (int u = 0; u < 5; u++) l2_prefetch(prm.wmod + (size_t)(bid * 5 + u) * 3840 + 1280, 5120);
                }
                if (hw == 0) { l2_prefetch((const uint8_t*)prm.wo + (size_t)bid * 6400, 6400); l2_prefetch((const uint8_t*)prm.wg + (size_t)bid * 15360, 15360); }
                else { l2_prefetch((const uint8_t*)prm.wu + (size_t)bid * 15360, 15360); l2_prefetch((const uint8_t*)prm.wd + (size_t)bid * 15360, 15360); }
                mbar_wait_long(rank == 1 && hw == 1 ? BAR(B_KG) : BAR(B_PUB + hw * 6 + 0), 0);
                if (rank == 0) {
                    mbar_wait_long(BAR(B_PD + 0), 0);
                    bulk_push(sb + SM_KV + (5 - hw) * KV_BYTES, sb + SM_KV + hw * KV_BYTES, KV_BYTES, BAR(B_KVF + 3 - hw), 1);
                    if (hw == 1) {
                        mbar_wait_long(BAR(B_PUB + 0), 0);
                        if (rb >= 2) mbar_wait_long(BAR(B_KVF + 1), 0);
                        bulk_store(g_kv + (size_t)(R * 8 + j) * KV_BYTES, sb + SM_KV + KV_BYTES, KV_BYTES);
                        bulk_store(g_kv + (size_t)((R - 1) * 8 + j) * KV_BYTES, sb + SM_KV, KV_BYTES);
                        bulk_commit_wait();
                        asm volatile("fence.acq_rel.gpu;" ::: "memory");
                        asm volatile("st.relaxed.gpu.global.u32 [%0], %1;" ::"l"(&g_flag[EV_KV][R][j]), "r"(tag << 2) : "memory");
                        asm volatile("st.relaxed.gpu.global.u32 [%0], %1;" ::"l"(&g_flag[EV_KV][R - 1][j]), "r"(tag << 2) : "memory");
                    }
                } else {
                    if (hw == 0) {
                        __nanosleep(600);
                        bulk_store(g_kv + (size_t)(R * 8 + j) * KV_BYTES, sb + SM_KV, KV_BYTES);
                        bulk_commit_wait();
                    }
                    st_flag(&g_flag[EV_KV][R][j], tag << 2);
                }
                mbar_arrive(BAR(B_KVS));
            }
            __syncwarp();
            const int slice = hw == 0 ? 80 + bid : (rank ? 208 + (bid >> 1) : 240);
            if (slice < 240) {
                const uint32_t buf = sb + SM_NS + hw * 20480;
                mbar_wait_long(BAR(B_M1 + hw), 0);
                float acc[8];
#pragma unroll
                for (int i = 0; i < 8; i++) acc[i] = 0.f;
#pragma unroll 2
                for (int u = 0; u < 40; u++) fma8(acc, lds128u(buf + u * 512 + lane * 16), lds32(sb + SM_SILU + (u * 16 + (lane >> 1)) * 4));
                float r = reduce8(acc, lane);
                float other = __shfl_xor_sync(~0u, r, 4);
                if ((lane & 6) == 0) {
                    int col = (lane & 1) * 8 + ((lane >> 4) & 1) * 4 + ((lane >> 3) & 1) * 2;
                    st_relaxed64(&g_mod[slice * 8 + (col >> 1)], ((unsigned long long)tag << 32) | pack2(r, other));
                }
            }
            if (rank == 1 && hw == 1) {
                mbar_wait_long(BAR(B_KVF + 3), 0); mbar_wait_long(BAR(B_KVF + 2), 0);
                if (lane < 2) mbar_arrive_cta(BAR(B_KVS), lane);
            }
            __syncwarp();
            if (lane < 2) mbar_arrive_cta(BAR(B_NS), lane);
            if (lane == 2) mbar_arrive(BAR(B_NSL));
            if (el) {
                const size_t idx = (size_t)(rb * 8 + j);
                if (hw == 0) {
                    mbar_wait_long(BAR(B_OS), 0);
                    asm volatile("fence.acq_rel.gpu;" ::: "memory");
                    asm volatile("st.relaxed.gpu.global.u32 [%0], %1;" ::"l"(&g_flag[EV_O][R][j]), "r"(tag << 2) : "memory");
                    asm volatile("st.relaxed.gpu.global.u32 [%0], %1;" ::"l"(&g_flag[EV_O][R + 1][j]), "r"(tag << 2) : "memory");
                }
                if (hw == 0) {
                    mbar_wait_long(BAR(B_X1S), 0);
                    asm volatile("fence.acq_rel.gpu;" ::: "memory");
                    asm volatile("st.relaxed.gpu.global.u32 [%0], %1;" ::"l"(&g_flag[EV_X1][R][j]), "r"(tag << 2) : "memory");
                    asm volatile("st.relaxed.gpu.global.u32 [%0], %1;" ::"l"(&g_flag[EV_X1][R + 1][j]), "r"(tag << 2) : "memory");
                    mbar_arrive(BAR(B_XS));
                } else mbar_wait_long(BAR(B_XS), 0);
                mbar_wait_long(BAR(B_H2 + hw), 0);
                bulk_store(g_h2 + (idx * 2 + hw) * O_BYTES, sb + SM_A4 + hw * O_BYTES, O_BYTES);
                bulk_commit_wait();
                st_flag(&g_flag[EV_X1][R][j], (tag << 2) + 1);
#pragma unroll 1
                for (int q = hw; q < 3; q += 2) {
                    mbar_wait_long(BAR(B_PUB + 3 + q), 0); mbar_wait(BAR(B_PUB + 9 + q), 0);
                    asm volatile("fence.acq_rel.gpu;" ::: "memory");
                    asm volatile("red.relaxed.gpu.global.max.u32 [%0], %1;" ::"l"(&g_flag[EV_HH][2 * rb][j]), "r"((tag << 2) + q) : "memory");
                }
            }
        }
    } else {
        asm volatile("setmaxnreg.inc.sync.aligned.u32 232;");
        asm volatile("barrier.cluster.arrive.relaxed.aligned;" ::: "memory");
        const int wg = __shfl_sync(~0u, warp >> 2, 0), wq = __shfl_sync(~0u, warp & 3, 0), g = lane >> 2, t = lane & 3;
        const uint32_t frag_off = (uint32_t)((lane >> 4) * 1024 + (wq * 16 + (lane & 15)) * 16);
        int j, rb; uint32_t tag;
        LnRow ln0, ln1;
        float aq[40], ak[40], av[40];
        {
            sts32u(sb + SM_ONES + tid * 4, 0x3f803f80u);
            if (tid >= 4 && tid < 8) sts32u(sb + SM_INFO + tid * 4, 0u);
            if (tid == 0) { sts32(sb + SM_INFO + 8, 0.035677408136300125f); sts32(sb + SM_INFO + 12, 0.22360679774997896f * 1.4426950408889634f); }
            fence_async_smem();
            read_info(j, rb, tag);
            if (wg == 0) {
                mbar_wait(BAR(B_C), 0);
#pragma unroll
                for (int u = 0; u < 5; u++) {
                    unsigned short cs; asm volatile("ld.shared.u16 %0, [%1];" : "=h"(cs) : "r"(sb + SM_P0 + 40960 + (u * 128 + tid) * 2) : "memory");
                    sts32(sb + SM_SILU + (u * 128 + tid) * 4, silu_bf(__ushort_as_bfloat16(cs)));
                }
                bar_sync(2, 128);
                if (uslice < 80) {
                    float acc[8];
#pragma unroll
                    for (int i = 0; i < 8; i++) acc[i] = 0.f;
#pragma unroll 1
                    for (int hf = 0; hf < 2; hf++) {
                        mbar_wait(hf ? BAR(B_M0B) : BAR(B_M0), 0);
#pragma unroll
                        for (int u = 0; u < 5; u++) fma8(acc, lds128u(sb + SM_P0 + (hf * 5 + u) * 2048 + tid * 16), lds32(sb + SM_SILU + ((hf * 5 + u) * 64 + (tid >> 1)) * 4));
                    }
                    float r = reduce8(acc, lane);
                    const int rcol = (lane & 1) * 8 + ((lane >> 4) & 1) * 4 + ((lane >> 3) & 1) * 2 + ((lane >> 2) & 1);
                    if ((lane & 2) == 0) sts32(sb + SM_MOD2 + (warp * 16 + rcol) * 4, r);
                    bar_sync(2, 128);
                    if (tid < 8) {
                        float a = 0.f, b = 0.f;
#pragma unroll
                        for (int ww = 0; ww < 4; ww++) { float2 v = lds64(sb + SM_MOD2 + (ww * 16 + tid * 2) * 4); a += v.x; b += v.y; }
                        st_relaxed64(&g_mod[uslice * 8 + tid], ((unsigned long long)tag << 32) | pack2(a, b));
                    }
                }
            } else {
                mbar_wait(BAR(B_XR), 0);
                const int lr = wq * 4 + (lane >> 3);
                uint4 xr[10];
#pragma unroll
                for (int u = 0; u < 10; u++) xr[u] = lds128u(sb + SM_P0 + 20480 + lr * 1280 + ((lane & 7) + 8 * u) * 16);
                float sum = 0.f;
#pragma unroll
                for (int u = 0; u < 10; u++) sum += (bf_lo(xr[u].x) + bf_hi(xr[u].x)) + (bf_lo(xr[u].y) + bf_hi(xr[u].y)) + (bf_lo(xr[u].z) + bf_hi(xr[u].z)) + (bf_lo(xr[u].w) + bf_hi(xr[u].w));
#pragma unroll
                for (int o = 1; o < 8; o <<= 1) sum += __shfl_xor_sync(~0u, sum, o);
                const float mean = sum * (1.f / DM);
                float sq = 0.f, sq2 = 0.f;
#pragma unroll
                for (int u = 0; u < 10; u++) {
                    uint32_t q4[4] = {xr[u].x, xr[u].y, xr[u].z, xr[u].w};
#pragma unroll
                    for (int e = 0; e < 4; e++) { float a = bf_lo(q4[e]) - mean, b = bf_hi(q4[e]) - mean; sq = fmaf(a, a, sq); sq2 = fmaf(b, b, sq2); }
                }
                sq += sq2;
#pragma unroll
                for (int o = 1; o < 8; o <<= 1) sq += __shfl_xor_sync(~0u, sq, o);
                if ((lane & 7) == 0) {
                    const LnRow k = ln_consts(mean, sq * (1.f / DM));
                    st_relaxed64(&g_st1[bid * 16 + lr], ((unsigned long long)((tag << 16) | (k.rl & 0xffffu)) << 32) | (k.rs & 0xffffu) | (k.nm & 0xffff0000u));
                }
            }
            if (uslice >= 80) __nanosleep(600);
            bar_sync(1, 256);
            {
                const uint64_t dz = make_desc(sb + SM_ONES, 0, 0, 0);
                const uint4 zz = lds128u(sb + SM_INFO + 16);
                const uint32_t z[4] = {zz.x, zz.y, zz.z, zz.w};
                wg_fence();
                wgmma_zero_n80(aq, z, dz + 0); wgmma_zero_n80(ak, z, dz + 8); wgmma_zero_n80(av, z, dz + 16);
                wg_commit(); wg_wait<0>();
                fence_regs(aq); fence_regs(ak); fence_regs(av);
            }
            const int r0 = rb * 128 + wg * 64 + wq * 16 + g;
            unsigned long long a0, a1, s0 = 0, s1 = 0, c0 = 0, c1 = 0;
            bool okm = tid >= 160, oks = false;
#pragma unroll 1
            for (int n = 0; n < SPIN_LIMIT; n++) {
                if (!okm) { ld_relaxed128(&g_mod[2 * tid], s0, s1); ld_relaxed128(&g_mod[320 + 2 * tid], c0, c1); }
                if (!oks) { a0 = ld_relaxed64(&g_st1[r0]); a1 = ld_relaxed64(&g_st1[r0 + 8]); }
                okm = okm || ((uint32_t)(s0 >> 32) == tag && (uint32_t)(s1 >> 32) == tag && (uint32_t)(c0 >> 32) == tag && (uint32_t)(c1 >> 32) == tag);
                oks = (uint32_t)(a0 >> 48) == (tag & 0xffffu) && (uint32_t)(a1 >> 48) == (tag & 0xffffu);
                if (okm && oks) break;
            }
            if (tid < 160) {
                const int w = (2 * tid) & 7;
                const uint32_t ma = sb + SM_MOD1 + ((tid >> 2) * 4 + (w & 3)) * 16 + (w >> 2) * 4, one2 = 0x3f803f80u;
                sts32u(ma, hfma2((uint32_t)c0, one2, one2)); sts32u(ma + 8, (uint32_t)s0);
                sts32u(ma + 16, hfma2((uint32_t)c1, one2, one2)); sts32u(ma + 24, (uint32_t)s1);
            }
            ln0.rs = __byte_perm((uint32_t)a0, 0, 0x1010); ln0.nm = __byte_perm((uint32_t)a0, 0, 0x3232); ln0.rl = __byte_perm((uint32_t)(a0 >> 32), 0, 0x1010);
            ln1.rs = __byte_perm((uint32_t)a1, 0, 0x1010); ln1.nm = __byte_perm((uint32_t)a1, 0, 0x3232); ln1.rl = __byte_perm((uint32_t)(a1 >> 32), 0, 0x1010);
            bar_sync(1, 256);
            if (tid < 2) mbar_arrive_cta(BAR(B_MC), tid);
        }
        const int R = 2 * rb + wg;
        uint32_t qf[32];
        {
            const int xrow = wg * 64 + wq * 16 + (lane & 15);
            const uint32_t xoff = xrow * 128, xsw = xrow & 7, xhi = lane >> 4;
            uint32_t a[2][4];
            uint32_t r0, r1, r2, r3; uint4 M;
            mbar_wait(BAR(B_PF), 0);
            ldsm4(sb + xoff + ((xhi ^ xsw) << 4), r0, r1, r2, r3);
            M = lds128u(sb + SM_MOD1 + t * 16);
#pragma unroll 1
            for (int kc = 0; kc < 10; kc++) {
                const uint32_t stg = sb + (kc & 3) * P1_STAGE;
                const uint64_t db0 = make_desc(stg + 16384, 6144, 512, 2);
#pragma unroll
                for (int ks = 0; ks < 4; ks++) {
                    ln_frag<true>(a[ks & 1], r0, r1, r2, r3, M, ln0, ln1);
                    const uint64_t db = db0 + (ks >> 1) * 1152 + (ks & 1) * 64;
                    wg_fence();
                    wgmma_rs_n80_tb1(aq, a[ks & 1][0], a[ks & 1][1], a[ks & 1][2], a[ks & 1][3], db, 1);
                    wgmma_rs_n80_tb1(ak, a[ks & 1][0], a[ks & 1][1], a[ks & 1][2], a[ks & 1][3], db + 128, 1);
                    wgmma_rs_n80_tb1(av, a[ks & 1][0], a[ks & 1][1], a[ks & 1][2], a[ks & 1][3], db + 256, 1);
                    wg_commit();
                    if (ks < 3) {
                        ldsm4(stg + xoff + ((((ks + 1) * 2 + xhi) ^ xsw) << 4), r0, r1, r2, r3);
                        M = lds128u(sb + SM_MOD1 + ((kc * 4 + ks + 1) * 4 + t) * 16);
                    } else if (kc < 9) {
                        mbar_wait(BAR(B_PF + ((kc + 1) & 3)), ((kc + 1) >> 2) & 1);
                        ldsm4(sb + ((kc + 1) & 3) * P1_STAGE + xoff + ((xhi ^ xsw) << 4), r0, r1, r2, r3);
                        M = lds128u(sb + SM_MOD1 + ((kc * 4 + 4) * 4 + t) * 16);
                    }
                    wg_wait<1>();
                    if (ks == 0 && kc >= 1 && kc <= 6 && (tid & 127) < 2) mbar_arrive_cta(BAR(B_PE + ((kc - 1) & 3)), tid & 1);
                }
            }
            wg_wait<0>();
            fence_regs(aq); fence_regs(ak); fence_regs(av);
            asm volatile("bar.arrive %0, 256;" ::"r"(5 - wg) : "memory");
            if ((tid & 127) < 2) mbar_arrive_cta(BAR(B_PD + 0), tid & 1);
            uint32_t kvp[44];
#pragma unroll
            for (int i = 0; i < 20; i++) kvp[i] = pack2(ak[2 * i], ak[2 * i + 1]);
#pragma unroll
            for (int p = 0; p < 2; p++) {
                const float* v = av + p * 20;
                uint32_t* d = kvp + 20 + p * 12;
                const uint32_t one = 0x00003f80u, ce = t == 2 ? one : 0u, co = t == 0 ? one : 0u;
                const uint32_t ml = pack2(v[8], v[9]), mh = pack2(v[10], v[11]);
#pragma unroll
                for (int i = 0; i < 4; i++) { d[i] = pack2(v[2 * i], v[2 * i + 1]); d[8 + i] = pack2(v[12 + 2 * i], v[13 + 2 * i]); }
                d[4] = t < 2 ? ml : ce; d[5] = t < 2 ? mh : ce; d[6] = t >= 2 ? ml : co; d[7] = t >= 2 ? mh : co;
            }
            if (rank == 1 && wg == 1) {
                uint8_t* kp = g_kv + (size_t)(R * 8 + j) * KV_BYTES + (wq * 16 + g) * 16 + t * 4;
#pragma unroll
                for (int i = 0; i < 44; i++) asm volatile("st.global.u32 [%0], %1;" ::"l"(kp + (i >> 1) * 1024 + (i & 1) * 128), "r"(kvp[i]) : "memory");
                __syncwarp();
                if (lane == 0) mbar_arrive(BAR(B_KG));
            }
            bar_sync(4 + wg, 256);
            const uint32_t kvs = sb + SM_KV + wg * KV_BYTES + frag_off;
#pragma unroll
            for (int b = 0; b < 22; b += 2) stsm4(kvs + b * 1024, kvp[2 * b], kvp[2 * b + 1], kvp[2 * b + 2], kvp[2 * b + 3]);
            fence_async_smem();
            __syncwarp();
            if (lane == 0) mbar_arrive(BAR(B_PUB + wg * 6 + 0));
            fence_regs(aq);
            const float qs = lds32(sb + SM_INFO + 12);
#pragma unroll
            for (int i = 0; i < 40; i++) aq[i] *= qs;
#pragma unroll
            for (int p = 0; p < 2; p++) {
                const float* vq = aq + p * 20;
                const float* vk = ak + p * 20;
                uint32_t* q = qf + p * 16;
#pragma unroll
                for (int r = 0; r < 2; r++) {
                    float w[5];
#pragma unroll
                    for (int b = 0; b < 5; b++) w[b] = fmaf(vq[b * 4 + r * 2], vk[b * 4 + r * 2], vq[b * 4 + r * 2 + 1] * vk[b * 4 + r * 2 + 1]);
                    q[6 + r] = pack2(-(w[0] + w[1] + (t < 2 ? w[2] : 0.f)), -10.f);
                    q[14 + r] = pack2(-(w[3] + w[4] + (t >= 2 ? w[2] : 0.f)), -10.f);
                }
                const uint32_t ml = pack2(vq[8], vq[9]), mh = pack2(vq[10], vq[11]);
#pragma unroll
                for (int i = 0; i < 4; i++) { q[i] = pack2(vq[2 * i], vq[2 * i + 1]); q[8 + i] = pack2(vq[12 + 2 * i], vq[13 + 2 * i]); }
                q[4] = t < 2 ? ml : 0u; q[5] = t < 2 ? mh : 0u; q[12] = t >= 2 ? ml : 0u; q[13] = t >= 2 ? mh : 0u;
            }
#pragma unroll
            for (int i = 0; i < 32; i++) asm volatile("" : "+r"(qf[i]));
        }
        {
            float o0[12], o1[12], o2[12], o3[12];
            float sa[32], sc[32];
            uint32_t pa[16], pb[16];
            const int dg = 2 * t - g;
            const uint32_t ones = sb + SM_ONES;
            auto kvslot = [&](int d) -> int { int e = wg - d; return e >= 0 ? e : 2 + ((-e - 1) ^ (rank << 1)); };
            auto kvaddr = [&](int d) -> uint32_t { return sb + SM_KV + kvslot(d) * KV_BYTES; };
            auto kvwait = [&](int d) { int sl = kvslot(d); mbar_wait(sl < 2 ? BAR(B_PUB + sl * 6 + 0) : BAR(B_KVF + sl - 2), 0); };
            const int dmax = R < 4 ? R : 4;
            kvwait(0);
            zero_regs(o0); zero_regs(o1); zero_regs(o2); zero_regs(o3);
            uint32_t kv = kvaddr(0);
            const uint32_t dmask = (dg <= 0 ? 0xffffu : 0u) | (dg + 1 <= 0 ? 0xffff0000u : 0u);
            fence_regs(o0); fence_regs(o1); fence_regs(o2); fence_regs(o3);
#pragma unroll
            for (int i = 0; i < 16; i++) { pb[i] = 0u; asm volatile("" : "+r"(pb[i])); }
            wg_fence();
            qk_mma<0>(sa, qf, kv, ones);
            wg_commit(); wg_wait<0>();
            fence_regs(sa);
            uint32_t ob[20];
            auto fin = [&](float (&e)[12], float (&od)[12], uint32_t* dst) {
                const int qb = lane & 28;
                float ie0 = rcp_fast(__shfl_sync(~0u, e[8], qb + 2)), ie1 = rcp_fast(__shfl_sync(~0u, e[10], qb + 2));
                float io0 = rcp_fast(__shfl_sync(~0u, od[0], qb)), io1 = rcp_fast(__shfl_sync(~0u, od[2], qb));
                dst[0] = pack2(e[0] * ie0, e[1] * ie0); dst[1] = pack2(e[2] * ie1, e[3] * ie1);
                dst[2] = pack2(e[4] * ie0, e[5] * ie0); dst[3] = pack2(e[6] * ie1, e[7] * ie1);
                dst[4] = t < 2 ? pack2(e[8] * ie0, e[9] * ie0) : pack2(od[0] * io0, od[1] * io0);
                dst[5] = t < 2 ? pack2(e[10] * ie1, e[11] * ie1) : pack2(od[2] * io1, od[3] * io1);
                dst[6] = pack2(od[4] * io0, od[5] * io0); dst[7] = pack2(od[6] * io1, od[7] * io1);
                dst[8] = pack2(od[8] * io0, od[9] * io0); dst[9] = pack2(od[10] * io1, od[11] * io1);
            };
            auto finish_o = [&](float (&e)[12], float (&od)[12], int hp) {
                fin(e, od, ob + hp * 10);
                uint8_t* op = g_o + (size_t)((rb * 8 + j) * 2 + wg) * O_BYTES + hp * 5120 + (wq * 16 + g) * 16 + t * 4;
#pragma unroll
                for (int i = 0; i < 10; i++) asm volatile("st.global.u32 [%0], %1;" ::"l"(op + (i >> 1) * 1024 + (i & 1) * 128), "r"(ob[hp * 10 + i]) : "memory");
            };
#pragma unroll
            for (int i = 0; i < 10; i++) ob[i] = 0;
            uint32_t kvp = kv;
            uint32_t mk[9];
#pragma unroll
            for (int kg = 0; kg < 5; kg++) mk[4 + kg] = kg <= wq ? ~0u : 0u;
#pragma unroll
            for (int kg = 0; kg < 4; kg++) mk[kg] = (dmask & mk[4 + kg]) | mk[5 + kg];
#pragma unroll 1
            for (int d = 0; d <= dmax; d++) {
                const int mm = (d & 3) == 0;
                if (d == 4) {
#pragma unroll
                    for (int i = 0; i < 9; i++) mk[i] = ~mk[i];
                }
#pragma unroll
                for (int i = 0; i < 9; i++) asm volatile("" : "+r"(mk[i]));
                att_fast<0>(sa, sc, pa, pb, o3, qf, kvp, kv, ones, mm, mk);
                att_fast<1>(sc, sa, pb, pa, o0, qf, kv, kv, ones, mm, mk);
                att_fast<2>(sa, sc, pa, pb, o1, qf, kv, kv, ones, mm, mk);
                uint32_t kvn = kv;
                if (d < dmax) { kvwait(d + 1); kvn = kvaddr(d + 1); }
                else { fence_regs(o0); fence_regs(o1); finish_o(o0, o1, 0); }
                att_fast<3>(sc, sa, pb, pa, o2, qf, kv, kvn, ones, mm, mk);
                kvp = kv; kv = kvn;
            }
            wg_fence();
            pv_mma(o3, pb, kvp + 19 * 1024);
            wg_commit();
            wg_wait<0>();
            fence_regs(o0); fence_regs(o1); fence_regs(o2); fence_regs(o3);
            mbar_wait(BAR(B_KVS), 0);
#pragma unroll 1
            for (int pass = 0;; pass++) {
                if (pass) finish_o(o0, o1, 0);
                finish_o(o2, o3, 1);
                const float lim = 1.2089258e24f, tiny = 8.2718061e-25f;
                const bool oke = (o0[8] + o0[10] + o2[8] + o2[10]) < lim && fminf(fminf(o0[8], o0[10]), fminf(o2[8], o2[10])) > tiny;
                const bool oko = (o1[0] + o1[2] + o3[0] + o3[2]) < lim && fminf(fminf(o1[0], o1[2]), fminf(o3[0], o3[2])) > tiny;
                uint32_t ex = 0;
#pragma unroll
                for (int i = 0; i < 20; i++) ex |= (ob[i] & 0x7f807f80u) + 0x00800080u;
                const bool bad = (t == 2 && !oke) || (t == 0 && !oko) || (ex & 0x80008000u) != 0;
                uint32_t anybad;
                asm volatile("{ .reg .pred p, q; setp.ne.u32 p, %1, 0; bar.red.or.pred q, 3, 256, p; selp.u32 %0, 1, 0, q; }" : "=r"(anybad) : "r"((uint32_t)bad) : "memory");
                if (pass || !__shfl_sync(~0u, anybad, 0)) break;
#pragma unroll 1
                for (int h = 0; h < 4; h++) {
                    float oc[12], m0 = -INFINITY, m1 = -INFINITY;
                    zero_regs(oc);
                    uint32_t q8[8];
#pragma unroll
                    for (int i = 0; i < 8; i++) { q8[i] = (h & 2) ? ((h & 1) ? qf[24 + i] : qf[16 + i]) : ((h & 1) ? qf[8 + i] : qf[i]); asm volatile("" : "+r"(q8[i])); }
                    float sx[32];
                    uint32_t px[16];
                    zero_regs(sx);
#pragma unroll 1
                    for (int d = 0; d <= dmax; d++) {
                        const uint32_t kb = kvaddr(d), mid = kb + ((h >> 1) * 5 + 2) * 1024;
                        fence_regs(sx);
                        wg_fence();
                        wgmma_rs_n64_tb0(sx, q8[0], q8[1], q8[2], q8[3], make_desc(mid + ((h & 1) ? 1024 : -2048), 1024, 128, 0), 0);
                        wgmma_rs_n64_tb0(sx, q8[4], q8[5], q8[6], q8[7], make_desc(mid, ones - mid, 128, 0), 1);
                        wg_commit(); wg_wait<0>();
                        fence_regs(sx);
                        mask_s(sx, d == 0 ? 1 : (d == 4 ? 2 : 0), wq, dg);
                        float a0, a1;
                        row_max(sx, m0, m1, a0, a1);
#pragma unroll
                        for (int i = 0; i < 12; i++) oc[i] *= (i & 2) ? a1 : a0;
#pragma unroll
                        for (int i = 0; i < 16; i++) { const float mm = (i & 1) ? m1 : m0; px[i] = pack2(ex2(sx[2 * i] - mm), ex2(sx[2 * i + 1] - mm)); }
#pragma unroll
                        for (int i = 0; i < 16; i++) asm volatile("" : "+r"(px[i]));
                        fence_regs(oc);
                        wg_fence();
                        pv_mma(oc, px, kb + (10 + 3 * h) * 1024);
                        wg_commit(); wg_wait<0>();
                        fence_regs(oc);
                    }
#pragma unroll
                    for (int i = 0; i < 12; i++) { o0[i] = h == 0 ? oc[i] : o0[i]; o1[i] = h == 1 ? oc[i] : o1[i]; o2[i] = h == 2 ? oc[i] : o2[i]; o3[i] = h == 3 ? oc[i] : o3[i]; }
                }
            }
            if (tid == 0) mbar_arrive(BAR(B_OS));

            const uint32_t os = sb + SM_T + wg * O_BYTES + frag_off;
#pragma unroll
            for (int b = 0; b < 10; b += 2) stsm4(os + b * 1024, ob[b * 2], ob[b * 2 + 1], ob[b * 2 + 2], ob[b * 2 + 3]);
            fence_async_smem();
            __syncwarp();
            if (lane == 0) mbar_arrive(BAR(B_PUB + wg * 6 + 1));
        }
        {
            float acc[40];
            zero_regs(acc);
            float xf[40], gf[20];
            zero_regs(xf); zero_regs(gf);
            mbar_wait(BAR(B_PUB + wg * 6 + 1), 0);
#pragma unroll 1
            for (int st = 0; st < 8; st++) {
                const int aslot = (0x21403210 >> (4 * st)) & 7;
                if (st > 0) mbar_wait(aslot == 4 ? BAR(B_XT) : BAR(B_TF + aslot), st > 4 ? 1 : 0);
                mbar_wait(BAR(B_WOF + st), 0);
                uint64_t da = make_desc(sb + SM_T + aslot * 20480 + wg * O_BYTES, 1024, 128, 0);
                uint64_t db = make_desc(sb + SM_WO + st * WO_SL, 2560, 256, 3);
                wg_fence();
#pragma unroll
                for (int ks = 0; ks < 5; ks++) wgmma_ss_n80_tb1(acc, da + ks * 128, db + ks * 32, 1);
                wg_commit();
                if (st == 0) {
                    wg_wait<0>();
                    if ((tid & 127) == 0) mbar_arrive(BAR(B_TE + 0));
                    mbar_wait(BAR(B_XT), 0);
#pragma unroll
                    for (int b = 0; b < 10; b += 2) {
                        uint32_t r[4];
                        ldsm4(sb + SM_XT + (wg * 64 + wq * 16 + (lane & 15)) * 160 + (b + (lane >> 4)) * 16, r[0], r[1], r[2], r[3]);
#pragma unroll
                        for (int e = 0; e < 4; e++) { xf[b * 4 + 2 * e] = bf_lo(r[e]); xf[b * 4 + 2 * e + 1] = bf_hi(r[e]); }
                    }
                    mbar_wait(BAR(B_MODS), 0);
#pragma unroll
                    for (int b = 0; b < 10; b++) { const uint32_t gt = lds32u(sb + SM_GV + (b * 4 + t) * 4); gf[2 * b] = bf_lo(gt); gf[2 * b + 1] = bf_hi(gt); }
                    fence_async_smem();
                    __syncwarp();
                    if (lane == 0) mbar_arrive(BAR(B_TE + 3));
                } else if (st == 2 || st == 3) { wg_wait<1>(); if ((tid & 127) == 0) mbar_arrive(BAR(B_TE + st - 1)); }
            }
            wg_wait<0>();
            fence_regs(acc);
            if ((tid & 127) < 2) mbar_arrive_cta(BAR(B_PD + 2), tid & 1);
            float s0 = 0.f, s1 = 0.f;
#pragma unroll
            for (int i = 0; i < 40; i++) xf[i] = fmaf(gf[(i >> 2) * 2 + (i & 1)], acc[i], xf[i]);
#pragma unroll
            for (int b = 0; b < 10; b++) { s0 += xf[b * 4] + xf[b * 4 + 1]; s1 += xf[b * 4 + 2] + xf[b * 4 + 3]; }
            s0 += __shfl_xor_sync(~0u, s0, 1); s1 += __shfl_xor_sync(~0u, s1, 1);
            s0 += __shfl_xor_sync(~0u, s0, 2); s1 += __shfl_xor_sync(~0u, s1, 2);
            s0 = __uint_as_float((__float_as_uint(s0 * (1.f / 80)) + 0x80u) & 0xffffff00u);
            s1 = __uint_as_float((__float_as_uint(s1 * (1.f / 80)) + 0x80u) & 0xffffff00u);
            float q0 = 0.f, q1 = 0.f, q2 = 0.f, q3 = 0.f;
#pragma unroll
            for (int b = 0; b < 10; b++) {
                float a = xf[b * 4] - s0, c = xf[b * 4 + 1] - s0; q0 = fmaf(a, a, q0); q2 = fmaf(c, c, q2);
                a = xf[b * 4 + 2] - s1; c = xf[b * 4 + 3] - s1; q1 = fmaf(a, a, q1); q3 = fmaf(c, c, q3);
            }
            q0 += q2; q1 += q3;
            q0 += __shfl_xor_sync(~0u, q0, 1); q1 += __shfl_xor_sync(~0u, q1, 1);
            q0 += __shfl_xor_sync(~0u, q0, 2); q1 += __shfl_xor_sync(~0u, q1, 2);
            if (t < 2) {
                const uint32_t mu = __float_as_uint(t ? s1 : s0), m2 = __float_as_uint(t ? q1 : q0) + 0x80u;
                st_relaxed64(&g_st2[(R * 8 + j) * 64 + wq * 16 + g * 2 + t], ((unsigned long long)(mu | (tag & 0xffu)) << 32) | (m2 & 0xffffff00u) | ((tag >> 8) & 0xffu));
            }
            uint32_t xr[20];
#pragma unroll
            for (int i = 0; i < 20; i++) xr[i] = pack2(xf[2 * i], xf[2 * i + 1]);
            {
                uint8_t* xp = g_x1 + (size_t)((rb * 8 + j) * 2 + wg) * O_BYTES + (wq * 16 + g) * 16 + t * 4;
#pragma unroll
                for (int i = 0; i < 20; i++) asm volatile("st.global.u32 [%0], %1;" ::"l"(xp + (i >> 1) * 1024 + (i & 1) * 128), "r"(xr[i]) : "memory");
            }
            bar_sync(1, 256);
            if (tid == 32) mbar_arrive(BAR(B_X1S));
            const uint32_t xs = sb + SM_A4 + wg * O_BYTES + frag_off;
#pragma unroll
            for (int b = 0; b < 10; b += 2) stsm4(xs + b * 1024, xr[b * 2], xr[b * 2 + 1], xr[b * 2 + 2], xr[b * 2 + 3]);
        }
        {
            float g0[32], g1[32], u0[32], u1[32], bg[32], bu[32];
            {
                const uint64_t dz = make_desc(sb + SM_ONES, 0, 0, 0);
                const uint4 zz = lds128u(sb + SM_INFO + 16);
                const uint32_t z[4] = {zz.x, zz.y, zz.z, zz.w};
                wg_fence();
                wgmma_zero_n64(g0, z, dz + 0); wgmma_zero_n64(g1, z, dz + 8); wgmma_zero_n64(u0, z, dz + 16);
                wgmma_zero_n64(u1, z, dz + 24); wgmma_zero_n64(bg, z, dz + 32); wgmma_zero_n64(bu, z, dz + 40);
                wg_commit(); wg_wait<0>();
                fence_regs(g0); fence_regs(g1); fence_regs(u0); fence_regs(u1); fence_regs(bg); fence_regs(bu);
            }
            {
                unsigned long long v[4];
                const unsigned long long* sp = &g_st2[(R * 8 + 2 * t) * 64 + wq * 16 + g * 2];
                const unsigned long long tm = 0x000000ff000000ffull, tv = ((unsigned long long)(tag & 0xffu) << 32) | ((tag >> 8) & 0xffu);
                bool ok0 = false, ok1 = false;
#pragma unroll 1
                for (int n = 0; n < SPIN_LIMIT; n++) {
                    if (!ok0) ld_relaxed128(sp, v[0], v[1]);
                    if (!ok1) ld_relaxed128(sp + 64, v[2], v[3]);
                    ok0 = (v[0] & tm) == tv && (v[1] & tm) == tv;
                    ok1 = (v[2] & tm) == tv && (v[3] & tm) == tv;
                    if (ok0 && ok1) break;
                }
                __syncwarp();
                float f[8];
#pragma unroll
                for (int i = 0; i < 4; i++) {
                    const unsigned long long w = v[(i & 1) * 2 + (i >> 1)];
                    f[2 * i] = __uint_as_float((uint32_t)(w >> 32) & 0xffffff00u); f[2 * i + 1] = __uint_as_float((uint32_t)w & 0xffffff00u);
                }
                float mu0 = f[0] + f[2], mu1 = f[4] + f[6];
                mu0 += __shfl_xor_sync(~0u, mu0, 1); mu1 += __shfl_xor_sync(~0u, mu1, 1);
                mu0 += __shfl_xor_sync(~0u, mu0, 2); mu1 += __shfl_xor_sync(~0u, mu1, 2);
                mu0 *= 0.125f; mu1 *= 0.125f;
                float d0 = f[0] - mu0, d1 = f[2] - mu0, d2 = f[4] - mu1, d3 = f[6] - mu1;
                float M0 = fmaf(80.f, fmaf(d0, d0, d1 * d1), f[1] + f[3]), M1 = fmaf(80.f, fmaf(d2, d2, d3 * d3), f[5] + f[7]);
                M0 += __shfl_xor_sync(~0u, M0, 1); M1 += __shfl_xor_sync(~0u, M1, 1);
                M0 += __shfl_xor_sync(~0u, M0, 2); M1 += __shfl_xor_sync(~0u, M1, 2);
                ln0 = ln_consts(mu0, M0 * (1.f / DM));
                ln1 = ln_consts(mu1, M1 * (1.f / DM));
            }
            if (tid < 2) mbar_arrive_cta(BAR(B_G), tid);
            uint32_t a[2][4];
            __syncwarp();
#pragma unroll 1
            for (int st2 = 0; st2 < 2; st2++) {
#pragma unroll
                for (int kk = 0; kk < 10; kk++) {
                    const int st = st2 * 2 + kk / 5, ks = kk % 5, bslot = kk >> 1;
                    const int jj = st == 0 ? j : (st - 1 < j ? st - 1 : st);
                    if (ks == 0 && st > 0) mbar_wait(BAR(B_AF + st), 0);
                    uint32_t r0, r1, r2, r3;
                    const uint32_t aa = sb + SM_A4 + st * 20480 + wg * O_BYTES + frag_off + ks * 2048;
                    ldsm4(aa, r0, r1, r2, r3);
                    uint4 M = lds128u(sb + SM_MOD2 + ((jj * 5 + ks) * 4 + t) * 16);
                    ln_frag<false>(a[kk & 1], r0, r1, r2, r3, M, ln0, ln1);
                    if (kk < 5 && st2 == 0) {
                        stsm4(aa, a[kk & 1][0], a[kk & 1][1], a[kk & 1][2], a[kk & 1][3]);
                        if (kk == 4) { fence_async_smem(); __syncwarp(); if (lane == 0) mbar_arrive(BAR(B_H2 + wg)); }
                    }
                    if (ks == 4) { __syncwarp(); if (lane == 0) mbar_arrive(BAR(B_AE + st)); }
                    if ((kk & 1) == 0) mbar_wait(BAR(B_BF + bslot), st2 & 1);
                    const uint64_t db = make_desc(sb + b4_off(bslot) + (kk & 1) * 12288, 2048, 1024, 1);
                    wg_fence();
                    wgmma_rs_n64_tb1(g0, a[kk & 1][0], a[kk & 1][1], a[kk & 1][2], a[kk & 1][3], db, 1);
                    wgmma_rs_n64_tb1(g1, a[kk & 1][0], a[kk & 1][1], a[kk & 1][2], a[kk & 1][3], db + 128, 1);
                    wgmma_rs_n64_tb1(u0, a[kk & 1][0], a[kk & 1][1], a[kk & 1][2], a[kk & 1][3], db + 384, 1);
                    wgmma_rs_n64_tb1(u1, a[kk & 1][0], a[kk & 1][1], a[kk & 1][2], a[kk & 1][3], db + 512, 1);
                    wgmma_rs_n64_tb1(bg, a[kk & 1][0], a[kk & 1][1], a[kk & 1][2], a[kk & 1][3], db + 256, 1);
                    wgmma_rs_n64_tb1(bu, a[kk & 1][0], a[kk & 1][1], a[kk & 1][2], a[kk & 1][3], db + 640, 1);
                    wg_commit();
                    wg_wait<1>();
                    if ((kk & 1) == 0 && (st2 | kk) && (tid & 127) < 2) mbar_arrive_cta(BAR(B_BE + (kk ? bslot - 1 : 4)), tid & 1);
                }
            }
            uint8_t* hp = g_hh + (size_t)((rb * 8 + j) * 3) * 16384 + wg * 8192 + (wq * 16 + g) * 16 + t * 4;
            auto geglu = [&](const float* gg, const float* uu, uint8_t* dst) {
                const float c3 = lds32(sb + SM_INFO + 8);
#pragma unroll
                for (int e = 0; e < 4; e++) {
                    float r[2];
#pragma unroll
                    for (int z = 0; z < 2; z++) {
                        const float gv = gg[e * 2 + z];
                        const float th = tanh_fast(gv * fmaf(gv * c3, gv, 0.7978845608028654f));
                        const float hu = gv * uu[e * 2 + z];
                        r[z] = fmaf(hu, th, hu);
                    }
                    asm volatile("st.global.u32 [%0], %1;" ::"l"(dst + (e >> 1) * 1024 + (e & 1) * 128), "r"(pack2(r[0], r[1])) : "memory");
                }
            };
            auto pass = [&](auto PC, float (&cg)[32], float (&cu)[32], float (&pg)[32], float (&pu)[32]) {
                constexpr int P = decltype(PC)::value;
                if (P > 0) { wg_wait<0>(); fence_regs(pg); fence_regs(pu); }
                const uint32_t sbp = __shfl_sync(~0u, sb, P);
#pragma unroll
                for (int s = 0; s < 4; s++) {
                    const int stage = 10 + P * 4 + s, bs = stage % 5;
                    if (P == 0) mbar_wait(BAR(B_AF + s), s ? 1 : 0);
                    mbar_wait(BAR(B_BF + bs), (stage / 5) & 1);
                    const uint64_t db = make_desc(sbp + b4_off(bs), 10240, 1024, 1);
                    const uint64_t da = make_desc(sbp + SM_A4 + s * 20480 + wg * O_BYTES, 1024, 128, 0);
                    wg_fence();
#pragma unroll
                    for (int ks = 0; ks < 5; ks++) {
                        wgmma_ss_n64_tb1(cg, da + ks * 128, db + ks * 128, 1);
                        wgmma_ss_n64_tb1(cu, da + ks * 128, db + 640 + ks * 128, 1);
                    }
                    wg_commit();
                    if (P < 2 || s < 3) {
                        wg_wait<1>();
                        if (stage <= 18) { if ((tid & 127) < 2) mbar_arrive_cta(BAR(B_BE + (stage - 1) % 5), tid & 1); }
                        else if ((tid & 127) < 4) mbar_arrive_cta(BAR(B_DE + (s - 1) * 2 + ((tid >> 1) & 1)), tid & 1);
                    }
                    if (P > 0) {
                        if (s < 2) {
#pragma unroll
                            for (int c = s * 2; c < s * 2 + 2; c++) geglu(pg + c * 8, pu + c * 8, hp + (P - 1) * 16384 + c * 2048);
                        }
                        if (s == 1) { __syncwarp(); if (lane == 0) mbar_arrive(BAR(B_PUB + wg * 6 + 3 + P - 1)); }
                    }
                }
            };
            pass(std::integral_constant<int, 0>{}, g0, u0, g0, u0);
            pass(std::integral_constant<int, 1>{}, g1, u1, g0, u0);
            pass(std::integral_constant<int, 2>{}, bg, bu, g1, u1);
            wg_wait<0>();
            fence_regs(bg); fence_regs(bu);
            if ((tid & 127) < 8) mbar_arrive_cta((tid & 127) < 2 ? BAR(B_PD + 3) : BAR(B_DE + 3 + ((tid & 127) >> 1)), tid & 1);
#pragma unroll
            for (int s = 0; s < 4; s++) geglu(bg + s * 8, bu + s * 8, hp + 2 * 16384 + s * 2048);
            __syncwarp();
            if (lane == 0) mbar_arrive(BAR(B_PUB + wg * 6 + 5));
        }
        {
            float acc[40];
            zero_regs(acc);
            int slot = 0; uint32_t ph = 0; int pslot = 0;
#pragma unroll 1
            for (int s = 0; s < 24; s++) {
                mbar_wait(BAR(B_DF + slot), ph);
                uint64_t da = make_desc(sb + da_off(slot) + wg * 8192, 1024, 128, 0);
                uint64_t db = make_desc(sb + db_off(slot), 2048, 256, 3);
                wg_fence();
#pragma unroll
                for (int ks = 0; ks < 4; ks++) wgmma_ss_n80_tb1(acc, da + ks * 128, db + ks * 32, 1);
                wg_commit();
                wg_wait<1>();
                if (s >= 1 && s <= 17 && (tid & 127) < 2) mbar_arrive_cta(BAR(B_DE + pslot), tid & 1);
                pslot = slot;
                if (++slot == D_NST) { slot = 0; ph ^= 1; }
            }
            uint32_t xr[20], gv[10];
            mbar_wait(BAR(B_X1), 0);
#pragma unroll
            for (int b = 0; b < 10; b += 2) ldsm4(sb + SM_X1 + wg * O_BYTES + frag_off + b * 1024, xr[b * 2], xr[b * 2 + 1], xr[b * 2 + 2], xr[b * 2 + 3]);
#pragma unroll
            for (int b = 0; b < 10; b++) gv[b] = lds32u(sb + SM_GV + 160 + (b * 4 + t) * 4);
            wg_wait<0>();
            fence_regs(acc);
#pragma unroll
            for (int i = 0; i < 20; i++) xr[i] = pack2(fmaf(bf_lo(gv[i >> 1]), acc[2 * i], bf_lo(xr[i])), fmaf(bf_hi(gv[i >> 1]), acc[2 * i + 1], bf_hi(xr[i])));
            const uint32_t os = sb + (wq >> 1) * 16384 + wg * 8192 + (wq & 1) * 2560;
#pragma unroll
            for (int b = 0; b < 10; b += 2) {
                const int blk = b;
                stsm4(os + (lane & 15) * 160 + (blk + (lane >> 4)) * 16, xr[b * 2], xr[b * 2 + 1], xr[b * 2 + 2], xr[b * 2 + 3]);
            }
            fence_async_smem();
            __syncwarp();
            if (elect()) {
                tma2d_store(&tm_out, os, 80 * j, R * 64 + wq * 16);
                asm volatile("cp.async.bulk.commit_group;" ::: "memory");
                asm volatile("cp.async.bulk.wait_group.read 0;" ::: "memory");
            }
            __syncwarp();
        }
    }
}

typedef CUresult (*EncodeFn)(CUtensorMap*, CUtensorMapDataType, cuuint32_t, void*, const cuuint64_t*, const cuuint64_t*, const cuuint32_t*,
                             const cuuint32_t*, CUtensorMapInterleave, CUtensorMapSwizzle, CUtensorMapL2promotion, CUtensorMapFloatOOBfill);

static void make_map(EncodeFn enc, CUtensorMap* m, const void* base, int rank, const cuuint64_t* dims, const cuuint64_t* strides, const cuuint32_t* box,
                     CUtensorMapSwizzle sw) {
    cuuint32_t es[5] = {1, 1, 1, 1, 1};
    enc(m, CU_TENSOR_MAP_DATA_TYPE_BFLOAT16, rank, (void*)base, dims, strides, box, es, CU_TENSOR_MAP_INTERLEAVE_NONE, sw,
        CU_TENSOR_MAP_L2_PROMOTION_L2_128B, CU_TENSOR_MAP_FLOAT_OOB_FILL_NONE);
}

extern "C" void kernel_launch(void* const* d_in, const int* in_sizes, int n_in, void* d_out, int out_size) {
    (void)in_sizes; (void)n_in; (void)out_size;
    Params p;
    p.x = (const bf16*)d_in[0]; p.wqkv = (const bf16*)d_in[1]; p.wo = (const bf16*)d_in[2];
    p.wg = (const bf16*)d_in[4]; p.wu = (const bf16*)d_in[5]; p.wd = (const bf16*)d_in[6];
    p.c = (const bf16*)d_in[7]; p.wmod = (const bf16*)d_in[8]; p.out = (bf16*)d_out;

    void* fn = nullptr;
    cudaDriverEntryPointQueryResult qr;
    cudaGetDriverEntryPoint("cuTensorMapEncodeTiled", &fn, cudaEnableDefault, &qr);
    EncodeFn enc = (EncodeFn)fn;
    CUtensorMap tx, tqm, tqr, tom, tg, tu, tdm, tmm, txt, tout, tg1, tu1;
    { cuuint64_t d[2] = {640, 2048}, s[1] = {1280}; cuuint32_t b[2] = {80, 128}; make_map(enc, &txt, p.x, 2, d, s, b, CU_TENSOR_MAP_SWIZZLE_NONE); }
    { cuuint64_t d[2] = {640, 2048}, s[1] = {1280}; cuuint32_t b[2] = {80, 16}; make_map(enc, &tout, p.out, 2, d, s, b, CU_TENSOR_MAP_SWIZZLE_NONE); }
    { cuuint64_t d[2] = {3840, 640}, s[1] = {7680}; cuuint32_t b[2] = {16, 160}; make_map(enc, &tmm, p.wmod, 2, d, s, b, CU_TENSOR_MAP_SWIZZLE_NONE); }
    { cuuint64_t d[2] = {640, 2048}, s[1] = {1280}; cuuint32_t b[2] = {64, 128}; make_map(enc, &tx, p.x, 2, d, s, b, CU_TENSOR_MAP_SWIZZLE_128B); }
    { cuuint64_t d[4] = {640, 640, 3, 2}, s[3] = {3840, 1280, 64}; cuuint32_t b[4] = {32, 32, 3, 2}; make_map(enc, &tqm, p.wqkv, 4, d, s, b, CU_TENSOR_MAP_SWIZZLE_64B); }
    { cuuint64_t d[3] = {640, 640, 3}, s[2] = {3840, 1280}; cuuint32_t b[3] = {16, 32, 3}; make_map(enc, &tqr, p.wqkv, 3, d, s, b, CU_TENSOR_MAP_SWIZZLE_64B); }
    { cuuint64_t d[3] = {640, 640, 5}, s[2] = {1280, 32}; cuuint32_t b[3] = {16, 80, 5}; make_map(enc, &tom, p.wo, 3, d, s, b, CU_TENSOR_MAP_SWIZZLE_32B); }
    { cuuint64_t d[3] = {64, 640, 24}, s[2] = {3072, 128}; cuuint32_t b3[3] = {64, 16, 3}, b1[3] = {64, 80, 1};
      make_map(enc, &tg, p.wg, 3, d, s, b3, CU_TENSOR_MAP_SWIZZLE_128B); make_map(enc, &tu, p.wu, 3, d, s, b3, CU_TENSOR_MAP_SWIZZLE_128B);
      make_map(enc, &tg1, p.wg, 3, d, s, b1, CU_TENSOR_MAP_SWIZZLE_128B); make_map(enc, &tu1, p.wu, 3, d, s, b1, CU_TENSOR_MAP_SWIZZLE_128B); }
    { cuuint64_t d[3] = {640, 1536, 5}, s[2] = {1280, 32}; cuuint32_t b[3] = {16, 64, 5}; make_map(enc, &tdm, p.wd, 3, d, s, b, CU_TENSOR_MAP_SWIZZLE_32B); }

    cudaFuncSetAttribute(fused_block_kernel, cudaFuncAttributeMaxDynamicSharedMemorySize, SM_TOTAL);
    fused_block_kernel<<<NCTA, 384, SM_TOTAL, cudaStreamPerThread>>>(tx, tqm, tqr, tom, tg, tu, tdm, tmm, txt, tout, tg1, tu1, p);
}
```
